```python
import torch

def _softmax(x, axis=-1):
    return torch.softmax(x, dim=axis)
def _gelu(x):
    return torch.nn.functional.gelu(x, approximate="tanh")
def _silu(x):
    return torch.nn.functional.silu(x)
def _sigmoid(x):
    return torch.sigmoid(x)
def _layernorm(x, axis=-1, eps=1e-5):
    m = x.mean(dim=axis, keepdim=True)
    v = x.var(dim=axis, keepdim=True, unbiased=False)
    return (x - m) / torch.sqrt(v + eps)
def _scatter_add(tgt, idx, src, axis=0):
    return tgt.clone().index_add_(axis, idx, src)
def _segment_sum(src, seg, n):
    out = torch.zeros((n,) + src.shape[1:], dtype=src.dtype)
    return out.index_add_(0, seg, src)
def _pad(x, pw):
    flat = tuple(v for pair in reversed(pw) for v in pair)
    return torch.nn.functional.pad(x, flat)

kernel_name = 'recurrent_scan__mha_block_cached__glu_gated_bilinear__decode'

def setup_inputs():

    _w = (lambda a: (lambda t: t.to(torch.bfloat16) if t.is_floating_point() else t)(torch.as_tensor(a)))
    def _A_setup():
        B, Sq, D = 8, 1, 512
        H, Sk, Dh = 32, 4096, 128
        return {
            "x": _w((lambda *s: torch.randn(*s, dtype=torch.bfloat16) * 0.2)(B, Sq, D)),
            "k_cache": _w((lambda *s: torch.randn(*s, dtype=torch.bfloat16) * 1.6)(B, H, Sk, Dh)),
            "v_cache": _w((lambda *s: torch.randn(*s, dtype=torch.bfloat16) * 1.6)(B, H, Sk, Dh)),
            "wq": _w((lambda *s: torch.randn(*s, dtype=torch.bfloat16) * 1.6)(D, H * Dh) * (D ** -0.5)),
            "wo": _w((lambda *s: torch.randn(*s, dtype=torch.bfloat16) * 1.6)(H * Dh, D) * ((H * Dh) ** -0.5)),
        }
    _A_in = _A_setup()

    def _B_setup():
        B, S, D, F = 8, 1, 512, 1792
        return {
            "x": _w((lambda *s: torch.randn(*s, dtype=torch.bfloat16) * 0.2)(B, S, D)),
            "w_gate": _w((lambda *s: torch.randn(*s, dtype=torch.bfloat16) * 0.8)(D, F) * (D ** -0.5)),
            "w_up": _w((lambda *s: torch.randn(*s, dtype=torch.bfloat16) * 0.8)(D, F) * (D ** -0.5)),
            "w_down": _w((lambda *s: torch.randn(*s, dtype=torch.bfloat16) * 0.8)(F, D) * (F ** -0.5)),
        }
    _B_in = _B_setup()

    return {
        "A_x": _A_in["x"],
        "A_k_cache": _A_in["k_cache"],
        "A_v_cache": _A_in["v_cache"],
        "A_wq": _A_in["wq"],
        "A_wo": _A_in["wo"],
        "B_x": _B_in["x"],
        "B_w_gate": _B_in["w_gate"],
        "B_w_up": _B_in["w_up"],
        "B_w_down": _B_in["w_down"],
    }

def reference(A_x, A_k_cache, A_v_cache, A_wq, A_wo, B_x, B_w_gate, B_w_up, B_w_down):
    def _A_ref(x, k_cache, v_cache, wq, wo):
        B, Sq, D = x.shape
        H, Dh = 32, 128
        q = (lambda x, *d: x.permute(*d))((x @ wq).reshape(B, Sq, H, Dh), 0, 2, 1, 3)
        scores = torch.einsum("bhqd,bhkd->bhqk", q, k_cache) * (Dh ** -0.5)
        p = _softmax(scores, axis=-1)
        o = torch.einsum("bhqk,bhkd->bhqd", p, v_cache)
        return (lambda x, *d: x.permute(*d))(o, 0, 2, 1, 3).reshape(B, Sq, H * Dh) @ wo

    def _B_ref(x, w_gate, w_up, w_down):
        g = torch.einsum("bsd,df->bsf", x, w_gate)
        u = torch.einsum("bsd,df->bsf", x, w_up)
        h = g * u
        return torch.einsum("bsf,fd->bsd", h, w_down)

    x = A_x
    xn = _layernorm(x, axis=-1)
    s = _A_ref(xn, A_k_cache, A_v_cache, A_wq, A_wo)
    g = _silu(_B_ref(xn, B_w_gate, B_w_up, B_w_down))
    return x + s * g
```

```cpp
#include <cuda_runtime.h>
#include <cuda_bf16.h>
#include <cuda.h>
#include <stdint.h>

namespace {

constexpr int kB = 8, kD = 512, kH = 32, kSk = 4096, kDh = 128, kF = 1792;
constexpr int kAttnCtas = 128, kGluCtas = 4, kGrid = kAttnCtas + kGluCtas;
constexpr int kThreads = 384;

constexpr int NST = 6;
constexpr int STAGE = 32768;
constexpr int TILES = kSk / 128;
constexpr int WO_POS = 6;
constexpr int kSrc = kH + kGluCtas;

constexpr int XN_STRIDE = 1040;
constexpr int HS_STRIDE = 912;
constexpr int OB_STRIDE = 272;

constexpr int OFF_SC = NST * STAGE;
constexpr int OFF_XN = OFF_SC + 8192;
constexpr int OFF_QS = OFF_XN + 8 * XN_STRIDE;
constexpr int OFF_OB = OFF_QS + 512;
constexpr int OFF_RED = OFF_OB + 8 * OB_STRIDE;
constexpr int OFF_BAR = OFF_RED + 64;
constexpr int SMEM_BYTES = OFF_BAR + 8 * (2 * NST + 1) + 8;

constexpr uint32_t kSpinLimit = 1u << 22;

__device__ uint32_t g_inbox[kB * 32 * kSrc * 16];

__device__ __forceinline__ uint32_t smem_u32(const void* p) { return (uint32_t)__cvta_generic_to_shared(p); }

__device__ __forceinline__ void mbar_init(uint32_t bar, uint32_t cnt) {
    asm volatile("mbarrier.init.shared.b64 [%0], %1;" ::"r"(bar), "r"(cnt) : "memory");
}
__device__ __forceinline__ void mbar_expect(uint32_t bar, uint32_t bytes) {
    asm volatile("mbarrier.arrive.expect_tx.shared.b64 _, [%0], %1;" ::"r"(bar), "r"(bytes) : "memory");
}
__device__ __forceinline__ void mbar_arrive(uint32_t bar) {
    asm volatile("mbarrier.arrive.shared.b64 _, [%0];" ::"r"(bar) : "memory");
}
__device__ __forceinline__ void mbar_wait(uint32_t bar, uint32_t parity) {
    uint32_t ok, it = 0;
    do {
        asm volatile("{.reg .pred p; mbarrier.try_wait.parity.shared.b64 p, [%1], %2; selp.u32 %0, 1, 0, p;}"
                     : "=r"(ok) : "r"(bar), "r"(parity) : "memory");
        if (++it > kSpinLimit) break;
    } while (!ok);
}
__device__ __forceinline__ void bulk_load(uint32_t dst, const void* src, uint32_t bytes, uint32_t bar, uint64_t pol) {
    asm volatile("cp.async.bulk.shared::cluster.global.mbarrier::complete_tx::bytes.L2::cache_hint [%0], [%1], %2, [%3], %4;"
                 ::"r"(dst), "l"(src), "r"(bytes), "r"(bar), "l"(pol) : "memory");
}
__device__ __forceinline__ void tma_load3(uint32_t dst, const CUtensorMap* m, int row, int grp, uint32_t bar) {
    asm volatile("cp.async.bulk.tensor.3d.shared::cluster.global.mbarrier::complete_tx::bytes [%0], [%1, {%3, %4, %5}], [%2];"
                 ::"r"(dst), "l"(m), "r"(bar), "r"(0), "r"(row), "r"(grp) : "memory");
}
__device__ __forceinline__ void ldsm4(uint32_t (&r)[4], uint32_t addr) {
    asm volatile("ldmatrix.sync.aligned.m8n8.x4.shared.b16 {%0,%1,%2,%3}, [%4];"
                 : "=r"(r[0]), "=r"(r[1]), "=r"(r[2]), "=r"(r[3]) : "r"(addr) : "memory");
}
__device__ __forceinline__ void ldsm4t(uint32_t (&r)[4], uint32_t addr) {
    asm volatile("ldmatrix.sync.aligned.m8n8.x4.trans.shared.b16 {%0,%1,%2,%3}, [%4];"
                 : "=r"(r[0]), "=r"(r[1]), "=r"(r[2]), "=r"(r[3]) : "r"(addr) : "memory");
}
__device__ __forceinline__ void mma16816(float (&c)[4], const uint32_t (&a)[4], uint32_t b0, uint32_t b1) {
    asm volatile("mma.sync.aligned.m16n8k16.row.col.f32.bf16.bf16.f32 {%0,%1,%2,%3}, {%4,%5,%6,%7}, {%8,%9}, {%0,%1,%2,%3};"
                 : "+f"(c[0]), "+f"(c[1]), "+f"(c[2]), "+f"(c[3])
                 : "r"(a[0]), "r"(a[1]), "r"(a[2]), "r"(a[3]), "r"(b0), "r"(b1));
}
__device__ __forceinline__ void bar_consumers() { asm volatile("bar.sync 1, 256;" ::: "memory"); }

__device__ __forceinline__ float bf16r(float x) { return __bfloat162float(__float2bfloat16_rn(x)); }
__device__ __forceinline__ uint32_t pack_bf16(float lo, float hi) {
    __nv_bfloat162 v = __floats2bfloat162_rn(lo, hi);
    return *reinterpret_cast<uint32_t*>(&v);
}
__device__ __forceinline__ float fdiv(float a, float b) {
    float r;
    asm("div.full.f32 %0, %1, %2;" : "=f"(r) : "f"(a), "f"(b));
    return r;
}
__device__ __forceinline__ float fsqrt(float a) {
    float r;
    asm("sqrt.approx.f32 %0, %1;" : "=f"(r) : "f"(a));
    return r;
}
__device__ __forceinline__ float bf_lo(uint32_t v) { return __uint_as_float(v << 16); }
__device__ __forceinline__ float bf_hi(uint32_t v) { return __uint_as_float(v & 0xffff0000u); }

__device__ __forceinline__ void sts16(uint32_t addr, float v) {
    __nv_bfloat16 h = __float2bfloat16_rn(v);
    asm volatile("st.shared.b16 [%0], %1;" ::"r"(addr), "h"(*reinterpret_cast<unsigned short*>(&h)) : "memory");
}
__device__ __forceinline__ void sts32(uint32_t addr, uint32_t v) {
    asm volatile("st.shared.b32 [%0], %1;" ::"r"(addr), "r"(v) : "memory");
}
__device__ __forceinline__ void sts128(uint32_t addr, uint32_t a, uint32_t b, uint32_t c, uint32_t d) {
    asm volatile("st.shared.v4.b32 [%0], {%1,%2,%3,%4};" ::"r"(addr), "r"(a), "r"(b), "r"(c), "r"(d) : "memory");
}
__device__ __forceinline__ uint32_t lds32(uint32_t addr) {
    uint32_t v;
    asm volatile("ld.shared.b32 %0, [%1];" : "=r"(v) : "r"(addr) : "memory");
    return v;
}
__device__ __forceinline__ uint4 lds128(uint32_t addr) {
    uint4 v;
    asm volatile("ld.shared.v4.b32 {%0,%1,%2,%3}, [%4];" : "=r"(v.x), "=r"(v.y), "=r"(v.z), "=r"(v.w) : "r"(addr) : "memory");
    return v;
}
__device__ __forceinline__ void inbox_store2(uint32_t* p, float a, float b) {
    uint32_t ua = __float_as_uint(a), ub = __float_as_uint(b);
    ua = ua ? ua : 0x80000000u;
    ub = ub ? ub : 0x80000000u;
    asm volatile("st.relaxed.gpu.global.v2.b32 [%0], {%1,%2};" ::"l"(p), "r"(ua), "r"(ub) : "memory");
}
__device__ __forceinline__ uint4 inbox_load4(const uint32_t* p) {
    uint4 v;
    asm volatile("ld.relaxed.gpu.global.v4.b32 {%0,%1,%2,%3}, [%4];" : "=r"(v.x), "=r"(v.y), "=r"(v.z), "=r"(v.w) : "l"(p) : "memory");
    return v;
}
__device__ __forceinline__ bool inbox_ready(const uint4& v) { return v.x && v.y && v.z && v.w; }

struct Ring {
    uint32_t full0, empty0, data0;
    uint32_t st, ph;
    __device__ __forceinline__ uint32_t acquire() {
        mbar_wait(full0 + 8 * st, ph);
        return data0 + st * STAGE;
    }
    __device__ __forceinline__ void release(int lane) {
        __syncwarp();
        if (lane == 0) mbar_arrive(empty0 + 8 * st);
        if (++st == NST) { st = 0; ph ^= 1; }
    }
};

struct Params {
    const __nv_bfloat16* x;
    const char* k;
    const char* v;
    __nv_bfloat16* out;
};

__device__ __forceinline__ void issue_tile(int i, uint32_t dst, uint32_t bar, const Params& p, uint64_t pol,
                                           const CUtensorMap* tm_wq, const CUtensorMap* tm_wo, const CUtensorMap* tm_wg,
                                           const CUtensorMap* tm_wu, const CUtensorMap* tm_wd) {
    const int cta = blockIdx.x;
    if (cta < kAttnCtas) {
        const int h = cta >> 2;
        mbar_expect(bar, STAGE);
        if (i < 4) {
            tma_load3(dst, tm_wq, 128 * i, 2 * h, bar);
        } else if (i >= 4 + WO_POS && i < 8 + WO_POS) {
            tma_load3(dst, tm_wo, 128 * h + 32 * (i - 4 - WO_POS), 0, bar);
        } else {
            const int c = i < 4 + WO_POS ? i - 4 : i - 8;
            const int bh = (2 * (cta & 3) + (c >> 6)) * kH + h;
            const char* base = (c & 32) ? p.v : p.k;
            bulk_load(dst, base + ((size_t)bh << 20) + ((size_t)(c & 31) << 15), STAGE, bar, pol);
        }
    } else {
        const int j = cta - kAttnCtas;
        if (i < 32) {
            mbar_expect(bar, 7 * 4096);
            tma_load3(dst, i < 16 ? tm_wg : tm_wu, 32 * (i & 15), 7 * j, bar);
        } else {
            mbar_expect(bar, STAGE);
            tma_load3(dst, tm_wd, 448 * j + 32 * (i - 32), 0, bar);
        }
    }
}

__device__ __forceinline__ void gemm_block32(float (&acc)[4][4], uint32_t wbase, uint32_t baddr, int lane) {
    const int mi = lane >> 3, r = lane & 7;
    uint32_t b[4];
    ldsm4(b, baddr);
#pragma unroll
    for (int ks = 0; ks < 2; ks++) {
#pragma unroll
        for (int mt = 0; mt < 4; mt++) {
            uint32_t a[4];
            ldsm4t(a, wbase + (16 * ks + (mi >> 1) * 8 + r) * 128 + (((2 * mt + (mi & 1)) ^ r) << 4));
            mma16816(acc[mt], a, b[2 * ks], b[2 * ks + 1]);
        }
    }
}

__global__ void __launch_bounds__(kThreads, 1)
fused_decode_kernel(const Params p,
                    const __grid_constant__ CUtensorMap tm_wq, const __grid_constant__ CUtensorMap tm_wo,
                    const __grid_constant__ CUtensorMap tm_wg, const __grid_constant__ CUtensorMap tm_wu,
                    const __grid_constant__ CUtensorMap tm_wd) {
    extern __shared__ __align__(1024) char smem[];
    const uint32_t sb = smem_u32(smem);
    const uint32_t bar_full = sb + OFF_BAR, bar_empty = bar_full + 8 * NST, bar_trig = bar_empty + 8 * NST;
    const int tid = threadIdx.x, warp = tid >> 5, lane = tid & 31;
    const int cta = blockIdx.x;
    const bool is_attn = cta < kAttnCtas;

    uint64_t pol = 0;
    uint4 xv0 = make_uint4(0, 0, 0, 0), xv1 = xv0;
    const int cw = warp - 4;
    const bool ln_warp = cw >= 0 && (!is_attn || cw < 2);
    if (tid == 0) {
#pragma unroll
        for (int i = 0; i < NST; i++) {
            mbar_init(bar_full + 8 * i, 1);
            mbar_init(bar_empty + 8 * i, 8);
        }
        mbar_init(bar_trig, 1);
        asm volatile("fence.mbarrier_init.release.cluster;" ::: "memory");
        asm volatile("createpolicy.fractional.L2::evict_first.b64 %0, 1.0;" : "=l"(pol));
        for (int i = 0; i < NST; i++)
            issue_tile(i, sb + i * STAGE, bar_full + 8 * i, p, pol, &tm_wq, &tm_wo, &tm_wg, &tm_wu, &tm_wd);
    } else if (ln_warp) {
        const int row = is_attn ? 2 * (cta & 3) + cw : cw;
        const uint4* xr = reinterpret_cast<const uint4*>(p.x + row * kD);
        xv0 = __ldg(xr + lane);
        xv1 = __ldg(xr + 32 + lane);
    }
    __syncthreads();

    if (warp < 4) {
        asm volatile("setmaxnreg.dec.sync.aligned.u32 72;");
        if (tid == 0) {
            const int n = is_attn ? 8 + 4 * TILES : 46;
            uint32_t st = 0, ph = 0;
            for (int i = NST; i < n; i++) {
                mbar_wait(bar_empty + 8 * st, ph);
                issue_tile(i, sb + st * STAGE, bar_full + 8 * st, p, pol, &tm_wq, &tm_wo, &tm_wg, &tm_wu, &tm_wd);
                if (++st == NST) { st = 0; ph ^= 1; }
            }
        } else if (warp == 1 && is_attn) {
            const int cg = cta & 31;
#pragma unroll 1
            for (int piece = 0; piece < 2; piece++) {
                const int b = 2 * (cta >> 5) + piece;
                uint32_t* box = g_inbox + (size_t)(b * 32 + cg) * kSrc * 16 + lane * 4;
                mbar_wait(bar_trig, piece);
                const int col = b * kD + cg * 16 + 2 * (lane & 3);
                const uint32_t xa = __ldg(reinterpret_cast<const uint32_t*>(p.x + col));
                const uint32_t xb = __ldg(reinterpret_cast<const uint32_t*>(p.x + col + 8));
                uint4 v[5];
                uint32_t pend = lane < 16 ? 31u : 15u;
                v[4] = make_uint4(0, 0, 0, 0);
                uint32_t it = 0;
                while (true) {
#pragma unroll
                    for (int i = 0; i < 5; i++)
                        if (pend >> i & 1) v[i] = inbox_load4(box + i * 128);
#pragma unroll
                    for (int i = 0; i < 5; i++)
                        if (inbox_ready(v[i])) pend &= ~(1u << i);
                    if (__all_sync(0xffffffffu, pend == 0)) break;
                    if (piece == 0) __nanosleep(1000);
                    if (++it > kSpinLimit) break;
                }
                float s[4], d[4];
                s[0] = (__uint_as_float(v[0].x) + __uint_as_float(v[1].x)) + (__uint_as_float(v[2].x) + __uint_as_float(v[3].x));
                s[1] = (__uint_as_float(v[0].y) + __uint_as_float(v[1].y)) + (__uint_as_float(v[2].y) + __uint_as_float(v[3].y));
                s[2] = (__uint_as_float(v[0].z) + __uint_as_float(v[1].z)) + (__uint_as_float(v[2].z) + __uint_as_float(v[3].z));
                s[3] = (__uint_as_float(v[0].w) + __uint_as_float(v[1].w)) + (__uint_as_float(v[2].w) + __uint_as_float(v[3].w));
                d[0] = __uint_as_float(v[4].x); d[1] = __uint_as_float(v[4].y);
                d[2] = __uint_as_float(v[4].z); d[3] = __uint_as_float(v[4].w);
#pragma unroll
                for (int o = 4; o < 32; o <<= 1) {
#pragma unroll
                    for (int i = 0; i < 4; i++) {
                        s[i] += __shfl_xor_sync(0xffffffffu, s[i], o);
                        if (o < 16) d[i] += __shfl_xor_sync(0xffffffffu, d[i], o);
                    }
                }
                if (lane < 4) {
                    const float xs[4] = {bf_lo(xa), bf_lo(xb), bf_hi(xa), bf_hi(xb)};
                    float r[4];
#pragma unroll
                    for (int i = 0; i < 4; i++) {
                        const float db = bf16r(d[i]);
                        const float gate = bf16r(fdiv(db, 1.0f + expf(-db)));
                        r[i] = xs[i] + bf16r(bf16r(s[i]) * gate);
                    }
                    *reinterpret_cast<uint32_t*>(p.out + col) = pack_bf16(r[0], r[2]);
                    *reinterpret_cast<uint32_t*>(p.out + col + 8) = pack_bf16(r[1], r[3]);
                }
#pragma unroll
                for (int i = 0; i < 5; i++)
                    if (i < 4 || lane < 16) *reinterpret_cast<uint4*>(box + i * 128) = make_uint4(0, 0, 0, 0);
            }
        }
    } else {
        asm volatile("setmaxnreg.inc.sync.aligned.u32 216;");
        const int g = lane >> 2, t = lane & 3, mi = lane >> 3, r = lane & 7;
        Ring ring{bar_full, bar_empty, sb, 0u, 0u};

        if (ln_warp) {
            const uint32_t w[8] = {xv0.x, xv0.y, xv0.z, xv0.w, xv1.x, xv1.y, xv1.z, xv1.w};
            float f[16];
            float sum = 0.f;
#pragma unroll
            for (int i = 0; i < 8; i++) {
                f[2 * i] = bf_lo(w[i]);
                f[2 * i + 1] = bf_hi(w[i]);
                sum += f[2 * i] + f[2 * i + 1];
            }
#pragma unroll
            for (int o = 16; o; o >>= 1) sum += __shfl_xor_sync(0xffffffffu, sum, o);
            const float mean = sum * (1.0f / kD);
            float var = 0.f;
#pragma unroll
            for (int i = 0; i < 16; i++) var += (f[i] - mean) * (f[i] - mean);
#pragma unroll
            for (int o = 16; o; o >>= 1) var += __shfl_xor_sync(0xffffffffu, var, o);
            const float mb = bf16r(mean);
            const float den = bf16r(fsqrt(bf16r(bf16r(var * (1.0f / kD)) + 1e-5f)));
            uint32_t o8[8];
#pragma unroll
            for (int i = 0; i < 8; i++) o8[i] = pack_bf16(fdiv(bf16r(f[2 * i] - mb), den), fdiv(bf16r(f[2 * i + 1] - mb), den));
            const uint32_t xr = sb + OFF_XN + cw * XN_STRIDE + lane * 16;
            sts128(xr, o8[0], o8[1], o8[2], o8[3]);
            sts128(xr + 512, o8[4], o8[5], o8[6], o8[7]);
        }
        bar_consumers();

        if (is_attn) {
            const int h = cta >> 2;
            {
                float qa[4] = {0.f, 0.f, 0.f, 0.f}, qb[4] = {0.f, 0.f, 0.f, 0.f};
                const uint32_t aoff = (cw >> 2) * 16384 + ((mi >> 1) * 8 + r) * 128 + (((2 * (cw & 3) + (mi & 1)) ^ r) << 4);
                const uint32_t boff = sb + OFF_XN + (r & 1) * XN_STRIDE + mi * 16;
#pragma unroll 1
                for (int i = 0; i < 4; i++) {
                    const uint32_t base = ring.acquire() + aoff;
#pragma unroll
                    for (int s2 = 0; s2 < 4; s2++) {
                        uint32_t b[4], a0[4], a1[4];
                        ldsm4(b, boff + i * 256 + s2 * 64);
                        ldsm4t(a0, base + s2 * 4096);
                        ldsm4t(a1, base + s2 * 4096 + 2048);
                        mma16816(qa, a0, b[0], b[1]);
                        mma16816(qb, a1, b[2], b[3]);
                    }
                    ring.release(lane);
                }
                if (t == 0) {
                    const uint32_t qd = sb + OFF_QS + (16 * cw + g) * 2;
                    sts16(qd, qa[0] + qb[0]);
                    sts16(qd + 256, qa[1] + qb[1]);
                    sts16(qd + 16, qa[2] + qb[2]);
                    sts16(qd + 256 + 16, qa[3] + qb[3]);
                }
                bar_consumers();
            }

            uint32_t wo[8][4][4];
            const bool diag = t == (g >> 1);
            const uint32_t sel0 = diag ? ((g & 1) ? 0x1044u : 0x4410u) : 0x4444u;
            const uint32_t sel1 = diag ? ((g & 1) ? 0x3244u : 0x4432u) : 0x4444u;
            const uint32_t sc = sb + OFF_SC + cw * 1024;
            const uint32_t red = sb + OFF_RED;
            const uint32_t koff = (16 * cw + (mi & 1) * 8 + r) * 256 + (((mi >> 1) ^ r) << 4);
            const uint32_t voff = (16 * cw + (mi >> 1) * 8 + r) * 256 + (((mi & 1) ^ r) << 4);

#pragma unroll 1
            for (int bb = 0; bb < 2; bb++) {
                float mx = -INFINITY;
                {
                    uint32_t bq[8][2];
#pragma unroll
                    for (int j = 0; j < 8; j++) {
                        bq[j][0] = lds32(sb + OFF_QS + bb * 256 + (((2 * j) ^ g) << 4) + t * 4);
                        bq[j][1] = lds32(sb + OFF_QS + bb * 256 + (((2 * j + 1) ^ g) << 4) + t * 4);
                    }
#pragma unroll 1
                    for (int tile = 0; tile < TILES; tile++) {
                        if (bb == 0 && tile == WO_POS) {
#pragma unroll
                            for (int i = 0; i < 4; i++) {
                                const uint32_t base = ring.acquire() + cw * 4096;
#pragma unroll
                                for (int ks = 0; ks < 2; ks++)
#pragma unroll
                                    for (int mt = 0; mt < 4; mt++)
                                        ldsm4t(wo[2 * i + ks][mt],
                                               base + (16 * ks + (mi >> 1) * 8 + r) * 128 + (((2 * mt + (mi & 1)) ^ r) << 4));
                                ring.release(lane);
                            }
                        }
                        const uint32_t base = ring.acquire();
                        float c0[4] = {0.f, 0.f, 0.f, 0.f}, c1[4] = {0.f, 0.f, 0.f, 0.f};
#pragma unroll
                        for (int j = 0; j < 8; j += 2) {
                            uint32_t a0[4], a1[4];
                            ldsm4(a0, base + (koff ^ (j << 5)));
                            ldsm4(a1, base + (koff ^ ((j + 1) << 5)));
                            mma16816(c0, a0, bq[j][0], bq[j][1]);
                            mma16816(c1, a1, bq[j + 1][0], bq[j + 1][1]);
                        }
                        ring.release(lane);
                        const float d0 = (g & 1) ? c0[1] + c1[1] : c0[0] + c1[0];
                        const float d1 = (g & 1) ? c0[3] + c1[3] : c0[2] + c1[2];
                        const float scale = 0.08838834764831845f;
                        const uint32_t sp = pack_bf16(bf16r(d0) * scale, bf16r(d1) * scale);
                        if (diag) {
                            mx = fmaxf(mx, fmaxf(bf_lo(sp), bf_hi(sp)));
                            sts32(sc + (tile * 8 + g) * 4, sp);
                        }
                    }
                }
                {
#pragma unroll
                    for (int o = 16; o; o >>= 1) mx = fmaxf(mx, __shfl_xor_sync(0xffffffffu, mx, o));
                    if (lane == 0) sts32(red + cw * 4, __float_as_uint(mx));
                    bar_consumers();
                    const uint4 m0 = lds128(red), m1 = lds128(red + 16);
                    mx = fmaxf(fmaxf(fmaxf(__uint_as_float(m0.x), __uint_as_float(m0.y)), fmaxf(__uint_as_float(m0.z), __uint_as_float(m0.w))),
                               fmaxf(fmaxf(__uint_as_float(m1.x), __uint_as_float(m1.y)), fmaxf(__uint_as_float(m1.z), __uint_as_float(m1.w))));
                    const uint4 s0 = lds128(sc + lane * 16), s1 = lds128(sc + 512 + lane * 16);
                    const uint32_t w[8] = {s0.x, s0.y, s0.z, s0.w, s1.x, s1.y, s1.z, s1.w};
                    float e[16];
                    float sum = 0.f;
                    const float log2e = 1.4426950408889634f;
#pragma unroll
                    for (int i = 0; i < 8; i++) {
                        e[2 * i] = exp2f((bf_lo(w[i]) - mx) * log2e);
                        e[2 * i + 1] = exp2f((bf_hi(w[i]) - mx) * log2e);
                        sum += e[2 * i] + e[2 * i + 1];
                    }
#pragma unroll
                    for (int o = 16; o; o >>= 1) sum += __shfl_xor_sync(0xffffffffu, sum, o);
                    if (lane == 0) sts32(red + 32 + cw * 4, __float_as_uint(sum));
                    bar_consumers();
                    const uint4 t0 = lds128(red + 32), t1 = lds128(red + 48);
                    const float tot = ((__uint_as_float(t0.x) + __uint_as_float(t0.y)) + (__uint_as_float(t0.z) + __uint_as_float(t0.w))) +
                                      ((__uint_as_float(t1.x) + __uint_as_float(t1.y)) + (__uint_as_float(t1.z) + __uint_as_float(t1.w)));
                    const float inv = fdiv(1.0f, tot);
                    sts128(sc + lane * 16, pack_bf16(e[0] * inv, e[1] * inv), pack_bf16(e[2] * inv, e[3] * inv),
                           pack_bf16(e[4] * inv, e[5] * inv), pack_bf16(e[6] * inv, e[7] * inv));
                    sts128(sc + 512 + lane * 16, pack_bf16(e[8] * inv, e[9] * inv), pack_bf16(e[10] * inv, e[11] * inv),
                           pack_bf16(e[12] * inv, e[13] * inv), pack_bf16(e[14] * inv, e[15] * inv));
                    __syncwarp();
                }
                float acc[8][4];
#pragma unroll
                for (int j = 0; j < 8; j++) acc[j][0] = acc[j][1] = acc[j][2] = acc[j][3] = 0.f;
#pragma unroll 1
                for (int tile = 0; tile < TILES; tile++) {
                    const uint32_t pw = lds32(sc + (tile * 8 + g) * 4);
                    const uint32_t b0 = __byte_perm(pw, 0, sel0), b1 = __byte_perm(pw, 0, sel1);
                    if (tile == TILES - 3 && tid == 128) mbar_arrive(bar_trig);
                    const uint32_t base = ring.acquire();
#pragma unroll
                    for (int j = 0; j < 8; j++) {
                        uint32_t a[4];
                        ldsm4t(a, base + (voff ^ (j << 5)));
                        mma16816(acc[j], a, b0, b1);
                    }
                    ring.release(lane);
                }
                {
                    float ev[8], od[8];
#pragma unroll
                    for (int j = 0; j < 8; j++) {
                        ev[j] = acc[j][0] + acc[j][3];
                        od[j] = acc[j][1] + acc[j][2];
                    }
#pragma unroll
                    for (int j = 0; j < 8; j += 2) {
                        ev[j] += __shfl_xor_sync(0xffffffffu, ev[j + 1], 1);
                        od[j] += __shfl_xor_sync(0xffffffffu, od[j + 1], 1);
                    }
#pragma unroll
                    for (int j = 0; j < 8; j += 4) {
                        ev[j] += __shfl_xor_sync(0xffffffffu, ev[j + 2], 2);
                        od[j] += __shfl_xor_sync(0xffffffffu, od[j + 2], 2);
                    }
                    const uint32_t od_addr = sb + OFF_OB + cw * OB_STRIDE + (16 * t + g) * 2;
                    sts16(od_addr, ev[0]);
                    sts16(od_addr + 16, od[0]);
                    sts16(od_addr + 128, ev[4]);
                    sts16(od_addr + 144, od[4]);
                }
                bar_consumers();
                {
                    float pc[4][4];
#pragma unroll
                    for (int mt = 0; mt < 4; mt++) pc[mt][0] = pc[mt][1] = pc[mt][2] = pc[mt][3] = 0.f;
#pragma unroll
                    for (int s2 = 0; s2 < 4; s2++) {
                        uint32_t b[4];
                        ldsm4(b, sb + OFF_OB + r * OB_STRIDE + s2 * 64 + mi * 16);
#pragma unroll
                        for (int mt = 0; mt < 4; mt++) mma16816(pc[mt], wo[2 * s2][mt], b[0], b[1]);
#pragma unroll
                        for (int mt = 0; mt < 4; mt++) mma16816(pc[mt], wo[2 * s2 + 1][mt], b[2], b[3]);
                    }
                    float lo[4], hi[4];
#pragma unroll
                    for (int mt = 0; mt < 4; mt++) {
                        lo[mt] = pc[mt][0] + pc[mt][1];
                        hi[mt] = pc[mt][2] + pc[mt][3];
                    }
                    const bool t1 = t & 1, t2 = t & 2;
                    const float yl0 = (t1 ? lo[1] : lo[0]) + __shfl_xor_sync(0xffffffffu, t1 ? lo[0] : lo[1], 1);
                    const float yl1 = (t1 ? lo[3] : lo[2]) + __shfl_xor_sync(0xffffffffu, t1 ? lo[2] : lo[3], 1);
                    const float yh0 = (t1 ? hi[1] : hi[0]) + __shfl_xor_sync(0xffffffffu, t1 ? hi[0] : hi[1], 1);
                    const float yh1 = (t1 ? hi[3] : hi[2]) + __shfl_xor_sync(0xffffffffu, t1 ? hi[2] : hi[3], 1);
                    const float zl = (t2 ? yl1 : yl0) + __shfl_xor_sync(0xffffffffu, t2 ? yl0 : yl1, 2);
                    const float zh = (t2 ? yh1 : yh0) + __shfl_xor_sync(0xffffffffu, t2 ? yh0 : yh1, 2);
                    const int b = 2 * (cta & 3) + bb;
                    inbox_store2(g_inbox + ((size_t)(b * 32 + 4 * cw + t) * kSrc + h) * 16 + 2 * g, zl, zh);
                }
            }
        } else {
            const int j = cta - kAttnCtas;
            float ga[4][4], ua[4][4];
#pragma unroll
            for (int mt = 0; mt < 4; mt++)
#pragma unroll
                for (int i = 0; i < 4; i++) ga[mt][i] = ua[mt][i] = 0.f;
            const uint32_t xb = sb + OFF_XN + r * XN_STRIDE + mi * 16;
#pragma unroll 1
            for (int i = 0; i < 16; i++) {
                const uint32_t base = ring.acquire();
                if (cw < 7) gemm_block32(ga, base + cw * 4096, xb + i * 64, lane);
                ring.release(lane);
            }
#pragma unroll 1
            for (int i = 0; i < 16; i++) {
                const uint32_t base = ring.acquire();
                if (cw < 7) gemm_block32(ua, base + cw * 4096, xb + i * 64, lane);
                ring.release(lane);
            }
            const uint32_t hs = sb + OFF_SC;
            if (cw < 7) {
#pragma unroll
                for (int mt = 0; mt < 4; mt++)
#pragma unroll
                    for (int i = 0; i < 4; i++)
                        sts16(hs + (2 * t + (i & 1)) * HS_STRIDE + (64 * cw + 16 * mt + g + (i >> 1) * 8) * 2,
                              bf16r(ga[mt][i]) * bf16r(ua[mt][i]));
            }
            bar_consumers();
#pragma unroll
            for (int mt = 0; mt < 4; mt++)
#pragma unroll
                for (int i = 0; i < 4; i++) ga[mt][i] = 0.f;
#pragma unroll 1
            for (int i = 0; i < 14; i++) {
                const uint32_t base = ring.acquire();
                gemm_block32(ga, base + cw * 4096, hs + r * HS_STRIDE + mi * 16 + i * 64, lane);
                ring.release(lane);
            }
#pragma unroll
            for (int mt = 0; mt < 4; mt++) {
                uint32_t* dst = g_inbox + ((size_t)(2 * t * 32 + 4 * cw + mt) * kSrc + kH + j) * 16 + 2 * g;
                inbox_store2(dst, ga[mt][0], ga[mt][2]);
                inbox_store2(dst + 32 * kSrc * 16, ga[mt][1], ga[mt][3]);
            }
        }
    }
}

typedef CUresult (*EncodeFn)(CUtensorMap*, CUtensorMapDataType, cuuint32_t, void*, const cuuint64_t*, const cuuint64_t*,
                             const cuuint32_t*, const cuuint32_t*, CUtensorMapInterleave, CUtensorMapSwizzle,
                             CUtensorMapL2promotion, CUtensorMapFloatOOBfill);

void encode_weight(EncodeFn fn, CUtensorMap* m, void* ptr, int rows, int cols, int box_rows, int box_grps) {
    cuuint64_t dims[3] = {64, (cuuint64_t)rows, (cuuint64_t)(cols / 64)};
    cuuint64_t strides[2] = {(cuuint64_t)cols * 2, 128};
    cuuint32_t box[3] = {64, (cuuint32_t)box_rows, (cuuint32_t)box_grps};
    cuuint32_t es[3] = {1, 1, 1};
    fn(m, CU_TENSOR_MAP_DATA_TYPE_BFLOAT16, 3, ptr, dims, strides, box, es, CU_TENSOR_MAP_INTERLEAVE_NONE,
       CU_TENSOR_MAP_SWIZZLE_128B, CU_TENSOR_MAP_L2_PROMOTION_NONE, CU_TENSOR_MAP_FLOAT_OOB_FILL_NONE);
}

}

extern "C" void kernel_launch(void* const* d_in, const int* in_sizes, int n_in, void* d_out, int out_size) {
    static EncodeFn encode = nullptr;
    if (!encode) {
        void* fn = nullptr;
        cudaDriverEntryPointQueryResult qr;
        cudaGetDriverEntryPoint("cuTensorMapEncodeTiled", &fn, cudaEnableDefault, &qr);
        encode = (EncodeFn)fn;
        cudaFuncSetAttribute(fused_decode_kernel, cudaFuncAttributeMaxDynamicSharedMemorySize, SMEM_BYTES);
    }
    Params p;
    p.x = (const __nv_bfloat16*)d_in[0];
    p.k = (const char*)d_in[1];
    p.v = (const char*)d_in[2];
    p.out = (__nv_bfloat16*)d_out;
    CUtensorMap tm_wq, tm_wo, tm_wg, tm_wu, tm_wd;
    encode_weight(encode, &tm_wq, d_in[3], kD, kH * kDh, 128, 2);
    encode_weight(encode, &tm_wo, d_in[4], kH * kDh, kD, 32, 8);
    encode_weight(encode, &tm_wg, d_in[6], kD, kF, 32, 7);
    encode_weight(encode, &tm_wu, d_in[7], kD, kF, 32, 7);
    encode_weight(encode, &tm_wd, d_in[8], kF, kD, 32, 8);
    fused_decode_kernel<<<kGrid, kThreads, SMEM_BYTES>>>(p, tm_wq, tm_wo, tm_wg, tm_wu, tm_wd);
}
```

```cpp
#include <cuda_runtime.h>
#include <cuda_bf16.h>
#include <cuda.h>
#include <stdint.h>

namespace {

constexpr int kB = 8, kD = 512, kH = 32, kSk = 4096, kDh = 128, kF = 1792;
constexpr int kAttnCtas = 128, kGluCtas = 4, kGrid = kAttnCtas + kGluCtas;
constexpr int kThreads = 384;

constexpr int NST = 6;
constexpr int STAGE = 32768;
constexpr int TILES = kSk / 128;
constexpr int WO_POS = 6;
constexpr int kAttnTiles = 8 + 4 * TILES;
constexpr int kGluTiles = 46;

#define LAST_SPLIT 8
#define PAR_PROLOGUE 0
#define NFREE1 16
#define WFREE1 6
#define NFREE2 24
#define WFREE2 4
#define PACE_W0X2 6
#define PACE_GAINX2 3

constexpr int XN_STRIDE = 1040;
constexpr int HS_STRIDE = 912;
constexpr int OB_STRIDE = 272;

constexpr int OFF_SC = NST * STAGE;
constexpr int OFF_XN = OFF_SC + 8192;
constexpr int OFF_XR = OFF_XN + 8 * XN_STRIDE;
constexpr int OFF_QS = OFF_XR + 2 * 1024;
constexpr int OFF_OB = OFF_QS + 512;
constexpr int OFF_RED = OFF_OB + 8 * OB_STRIDE;
constexpr int OFF_BAR = OFF_RED + 64;
constexpr int OFF_PACE = OFF_BAR + 8 * (2 * NST + 1 + LAST_SPLIT);
constexpr int SMEM_BYTES = OFF_PACE + 8;

constexpr uint32_t kSpinLimit = 1u << 22;

__device__ __align__(1024) float4 g_acc[kB * 256];
__device__ __align__(1024) float2 g_glu[kGluCtas * kB * 256];
#define LANDED_OFF 0
__device__ __align__(1024) uint32_t g_sync_pad[4096];
#define g_landed g_sync_pad[LANDED_OFF]
#define g_stage g_sync_pad[LANDED_OFF + 64]
constexpr uint32_t kStageWrap = 2 * kGluCtas + kAttnCtas - 1;

#define TS(k) do {} while (0)

__device__ __forceinline__ uint32_t smem_u32(const void* p) { return (uint32_t)__cvta_generic_to_shared(p); }

__device__ __forceinline__ void mbar_init(uint32_t bar, uint32_t cnt) {
    asm volatile("mbarrier.init.shared.b64 [%0], %1;" ::"r"(bar), "r"(cnt) : "memory");
}
__device__ __forceinline__ void mbar_expect(uint32_t bar, uint32_t bytes) {
    asm volatile("mbarrier.arrive.expect_tx.shared.b64 _, [%0], %1;" ::"r"(bar), "r"(bytes) : "memory");
}
__device__ __forceinline__ void mbar_arrive(uint32_t bar) {
    asm volatile("mbarrier.arrive.shared.b64 _, [%0];" ::"r"(bar) : "memory");
}
__device__ __forceinline__ void mbar_wait(uint32_t bar, uint32_t parity) {
    uint32_t ok, it = 0;
    do {
        asm volatile("{.reg .pred p; mbarrier.try_wait.parity.shared.b64 p, [%1], %2; selp.u32 %0, 1, 0, p;}"
                     : "=r"(ok) : "r"(bar), "r"(parity) : "memory");
        if (++it > kSpinLimit) break;
    } while (!ok);
}
__device__ __forceinline__ bool mbar_test(uint32_t bar, uint32_t parity) {
    uint32_t ok;
    asm volatile("{.reg .pred p; mbarrier.test_wait.parity.shared.b64 p, [%1], %2; selp.u32 %0, 1, 0, p;}"
                 : "=r"(ok) : "r"(bar), "r"(parity) : "memory");
    return ok;
}
__device__ __forceinline__ void bulk_load(uint32_t dst, const void* src, uint32_t bytes, uint32_t bar, uint64_t pol) {
    asm volatile("cp.async.bulk.shared::cluster.global.mbarrier::complete_tx::bytes.L2::cache_hint [%0], [%1], %2, [%3], %4;"
                 ::"r"(dst), "l"(src), "r"(bytes), "r"(bar), "l"(pol) : "memory");
}
__device__ __forceinline__ void tma_load3(uint32_t dst, const CUtensorMap* m, int row, int grp, uint32_t bar) {
    asm volatile("cp.async.bulk.tensor.3d.shared::cluster.global.mbarrier::complete_tx::bytes [%0], [%1, {%3, %4, %5}], [%2];"
                 ::"r"(dst), "l"(m), "r"(bar), "r"(0), "r"(row), "r"(grp) : "memory");
}
__device__ __forceinline__ void ldsm4(uint32_t (&r)[4], uint32_t addr) {
    asm volatile("ldmatrix.sync.aligned.m8n8.x4.shared.b16 {%0,%1,%2,%3}, [%4];"
                 : "=r"(r[0]), "=r"(r[1]), "=r"(r[2]), "=r"(r[3]) : "r"(addr) : "memory");
}
__device__ __forceinline__ void ldsm4t(uint32_t (&r)[4], uint32_t addr) {
    asm volatile("ldmatrix.sync.aligned.m8n8.x4.trans.shared.b16 {%0,%1,%2,%3}, [%4];"
                 : "=r"(r[0]), "=r"(r[1]), "=r"(r[2]), "=r"(r[3]) : "r"(addr) : "memory");
}
__device__ __forceinline__ void mma16816(float (&c)[4], const uint32_t (&a)[4], uint32_t b0, uint32_t b1) {
    asm volatile("mma.sync.aligned.m16n8k16.row.col.f32.bf16.bf16.f32 {%0,%1,%2,%3}, {%4,%5,%6,%7}, {%8,%9}, {%0,%1,%2,%3};"
                 : "+f"(c[0]), "+f"(c[1]), "+f"(c[2]), "+f"(c[3])
                 : "r"(a[0]), "r"(a[1]), "r"(a[2]), "r"(a[3]), "r"(b0), "r"(b1));
}
__device__ __forceinline__ void bar_consumers() { asm volatile("bar.sync 1, 256;" ::: "memory"); }

__device__ __forceinline__ uint32_t pack_bf16(float lo, float hi) {
    uint32_t r;
    asm("cvt.rn.bf16x2.f32 %0, %1, %2;" : "=r"(r) : "f"(hi), "f"(lo));
    return r;
}
__device__ __forceinline__ float bf16r(float x) { return __uint_as_float(pack_bf16(0.f, x)); }
__device__ __forceinline__ float fdiv(float a, float b) {
    float r;
    asm("div.full.f32 %0, %1, %2;" : "=f"(r) : "f"(a), "f"(b));
    return r;
}
__device__ __forceinline__ float fsqrt(float a) {
    float r;
    asm("sqrt.approx.f32 %0, %1;" : "=f"(r) : "f"(a));
    return r;
}
__device__ __forceinline__ float bf_lo(uint32_t v) { return __uint_as_float(v << 16); }
__device__ __forceinline__ float bf_hi(uint32_t v) { return __uint_as_float(v & 0xffff0000u); }

__device__ __forceinline__ void sts16(uint32_t addr, float v) {
    asm volatile("st.shared.b16 [%0], %1;" ::"r"(addr), "h"((unsigned short)pack_bf16(v, 0.f)) : "memory");
}
__device__ __forceinline__ void sts32(uint32_t addr, uint32_t v) {
    asm volatile("st.shared.b32 [%0], %1;" ::"r"(addr), "r"(v) : "memory");
}
__device__ __forceinline__ void sts128(uint32_t addr, uint32_t a, uint32_t b, uint32_t c, uint32_t d) {
    asm volatile("st.shared.v4.b32 [%0], {%1,%2,%3,%4};" ::"r"(addr), "r"(a), "r"(b), "r"(c), "r"(d) : "memory");
}
__device__ __forceinline__ uint32_t lds32(uint32_t addr) {
    uint32_t v;
    asm volatile("ld.shared.b32 %0, [%1];" : "=r"(v) : "r"(addr) : "memory");
    return v;
}
__device__ __forceinline__ uint4 lds128(uint32_t addr) {
    uint4 v;
    asm volatile("ld.shared.v4.b32 {%0,%1,%2,%3}, [%4];" : "=r"(v.x), "=r"(v.y), "=r"(v.z), "=r"(v.w) : "r"(addr) : "memory");
    return v;
}
__device__ __forceinline__ uint32_t lds16(uint32_t addr) {
    unsigned short v;
    asm volatile("ld.shared.b16 %0, [%1];" : "=h"(v) : "r"(addr) : "memory");
    return v;
}
__device__ __forceinline__ void out_arrive(float4* slot, float s0, float s1, uint32_t x_addr, unsigned short* outp) {
    float4 o;
    asm volatile("atom.relaxed.gpu.global.add.v4.f32 {%0,%1,%2,%3}, [%4], {%5,%6,%7,%8};"
                 : "=f"(o.x), "=f"(o.y), "=f"(o.z), "=f"(o.w)
                 : "l"(slot), "f"(s0), "f"(s1), "f"(65536.f), "f"(0.f) : "memory");
    const float x0 = __uint_as_float(lds16(x_addr) << 16), x1 = __uint_as_float(lds16(x_addr + 16) << 16);
    if (o.z >= 65536.f * (kH - 1)) {
        const float g0 = __uint_as_float(__float_as_uint(o.z + 8388608.f) << 16);
        const float g1 = __uint_as_float(__float_as_uint(o.w + 8388608.f) << 16);
        const uint32_t r = pack_bf16(x0 + bf16r(bf16r(o.x + s0) * g0), x1 + bf16r(bf16r(o.y + s1) * g1));
        outp[0] = (unsigned short)r;
        outp[8] = (unsigned short)(r >> 16);
    }
}
__device__ __forceinline__ void fence_gpu() { asm volatile("fence.acq_rel.gpu;" ::: "memory"); }
__device__ __forceinline__ uint32_t load_relaxed(const uint32_t* p) {
    uint32_t v;
    asm volatile("ld.relaxed.gpu.global.u32 %0, [%1];" : "=r"(v) : "l"(p) : "memory");
    return v;
}
__device__ __forceinline__ void red_inc(uint32_t* p, uint32_t limit) {
    asm volatile("red.relaxed.gpu.global.inc.u32 [%0], %1;" ::"l"(p), "r"(limit) : "memory");
}

struct Ring {
    uint32_t full0, empty0, data0;
    uint32_t st, ph;
    __device__ __forceinline__ uint32_t acquire() {
        mbar_wait(full0 + 8 * st, ph);
        return data0 + st * STAGE;
    }
    __device__ __forceinline__ void release(int lane) {
        __syncwarp();
        if (lane == 0) mbar_arrive(empty0 + 8 * st);
        if (++st == NST) { st = 0; ph ^= 1; }
    }
};

struct Params {
    const __nv_bfloat16* x;
    const char* k;
    const char* v;
    __nv_bfloat16* out;
};

__device__ __forceinline__ void issue_tile(int cta, int i, uint32_t dst, uint32_t bar, const Params& p, uint64_t pol,
                                           const CUtensorMap* tm_wq, const CUtensorMap* tm_wo, const CUtensorMap* tm_wg,
                                           const CUtensorMap* tm_wu, const CUtensorMap* tm_wd) {
    if (cta < kAttnCtas) {
        const int h = cta >> 2;
        mbar_expect(bar, STAGE);
        if (i < 4) {
            tma_load3(dst, tm_wq, 128 * i, 2 * h, bar);
        } else if (i >= 4 + WO_POS && i < 8 + WO_POS) {
            tma_load3(dst, tm_wo, 128 * h + 32 * (i - 4 - WO_POS), 0, bar);
        } else {
            const int c = i < 4 + WO_POS ? i - 4 : i - 8;
            const int bh = ((cta & 3) + 4 * (c >> 6)) * kH + h;
            const char* base = (c & 32) ? p.v : p.k;
            bulk_load(dst, base + ((size_t)bh << 20) + ((size_t)(c & 31) << 15), STAGE, bar, pol);
        }
    } else {
        const int j = cta - kAttnCtas;
        if (i < 32) {
            mbar_expect(bar, 7 * 4096);
            tma_load3(dst, i < 16 ? tm_wg : tm_wu, 32 * (i & 15), 7 * j, bar);
        } else {
            mbar_expect(bar, STAGE);
            tma_load3(dst, tm_wd, 448 * j + 32 * (i - 32), 0, bar);
        }
    }
}

__device__ __forceinline__ void gemm_block32(float (&acc)[4][4], uint32_t wbase, uint32_t baddr, int lane) {
    const int mi = lane >> 3, r = lane & 7;
    uint32_t b[4];
    ldsm4(b, baddr);
#pragma unroll
    for (int ks = 0; ks < 2; ks++) {
#pragma unroll
        for (int mt = 0; mt < 4; mt++) {
            uint32_t a[4];
            ldsm4t(a, wbase + (16 * ks + (mi >> 1) * 8 + r) * 128 + (((2 * mt + (mi & 1)) ^ r) << 4));
            mma16816(acc[mt], a, b[2 * ks], b[2 * ks + 1]);
        }
    }
}

__global__ void __launch_bounds__(kThreads, 1)
fused_decode_kernel(const Params p,
                    const __grid_constant__ CUtensorMap tm_wq, const __grid_constant__ CUtensorMap tm_wo,
                    const __grid_constant__ CUtensorMap tm_wg, const __grid_constant__ CUtensorMap tm_wu,
                    const __grid_constant__ CUtensorMap tm_wd) {
    extern __shared__ __align__(1024) char smem[];
    const uint32_t sb = smem_u32(smem);
    const uint32_t bar_full = sb + OFF_BAR, bar_empty = bar_full + 8 * NST;
    const uint32_t bar_gate = bar_empty + 8 * NST, bar_last = bar_gate + 8;
    const int tid = threadIdx.x, warp = tid >> 5, lane = tid & 31;
    const int blk33 = blockIdx.x / 33;
    const bool is_attn = blockIdx.x - blk33 * 33 != 32;
    const int cta = is_attn ? blockIdx.x - blk33 : kAttnCtas + blk33;

    uint64_t pol;
    asm volatile("createpolicy.fractional.L2::evict_first.b64 %0, 1.0;" : "=l"(pol));
    uint4 xv0 = make_uint4(0, 0, 0, 0), xv1 = xv0;
    const int cw = warp - 4;
    const bool ln_warp = is_attn ? cw >= 6 : cw >= 0;
    const int ln_row = is_attn ? cw - 6 : cw;
    if (tid == 0) TS(0);
    if (tid == 0) {
#pragma unroll
        for (int i = 0; i < NST; i++) mbar_init(bar_full + 8 * i, 1);
        asm volatile("fence.mbarrier_init.release.cluster;" ::: "memory");
#pragma unroll 1
        for (int i = 0; i < NST; i++)
            issue_tile(cta, i, sb + i * STAGE, bar_full + 8 * i, p, pol, &tm_wq, &tm_wo, &tm_wg, &tm_wu, &tm_wd);
    }
    if (tid == 0) TS(1);
    if (ln_warp) {
        const uint4* xr = reinterpret_cast<const uint4*>(p.x + (is_attn ? (cta & 3) + 4 * ln_row : ln_row) * kD);
        xv0 = __ldg(xr + lane);
        xv1 = __ldg(xr + 32 + lane);
    }
    if (tid == 6 * 32) {
#pragma unroll
        for (int i = 0; i < NST; i++) mbar_init(bar_empty + 8 * i, 8);
        mbar_init(bar_gate, 1);
#pragma unroll
        for (int i = 0; i < LAST_SPLIT; i++) mbar_init(bar_last + 8 * i, 1);
        sts32(sb + OFF_PACE, 0);
        sts32(sb + OFF_PACE + 4, 0);
        asm volatile("fence.mbarrier_init.release.cluster;" ::: "memory");
    }
    __syncthreads();

    if (warp < 4) {
        asm volatile("setmaxnreg.dec.sync.aligned.u32 40;");
        if (tid == 0) {
            const int n = is_attn ? kAttnTiles : kGluTiles;
            const int ntrack = is_attn ? n - 1 : 0;
            int i = NST, c = 0;
            uint32_t ist = 0, iph = 0, cst = 0, cph = 0, it = 0;
            while (i < n || c < ntrack) {
                if (i == n) mbar_wait(bar_full + 8 * cst, cph);
                if (i == n || (c < i && mbar_test(bar_full + 8 * cst, cph))) {
                    c++;
                    if (++cst == NST) { cst = 0; cph ^= 1; }
                    if (is_attn) red_inc(&g_landed, kAttnCtas * (kAttnTiles - 1) - 1);
                }
                if (i < n) {
                    const int fl = i - c;
                    bool go;
                    if (i < NFREE1) go = fl < WFREE1;
                    else if (i < NFREE2 || !is_attn) go = fl < WFREE2;
                    else go = fl == 0 && i == n - 1 ? true
                            : fl < NST && 256 * fl < 128 * PACE_W0X2 + PACE_GAINX2 * ((int)lds32(sb + OFF_PACE) - 128 * c);
                    const bool timeout = ++it > (kSpinLimit << 4);
                    if ((go && mbar_test(bar_empty + 8 * ist, iph)) || timeout) {
                        if (is_attn && i == n - 1) {
                            const char* src = p.v + ((size_t)(((cta & 3) + 4) * kH + (cta >> 2)) << 20) + ((size_t)(TILES - 1) << 15);
#pragma unroll 1
                            for (int j = 0; j < LAST_SPLIT; j++) {
                                mbar_expect(bar_last + 8 * j, STAGE / LAST_SPLIT);
                                bulk_load(sb + ist * STAGE + j * (STAGE / LAST_SPLIT), src + j * (STAGE / LAST_SPLIT),
                                          STAGE / LAST_SPLIT, bar_last + 8 * j, pol);
                            }
                            sts32(sb + OFF_PACE + 4, 1);
                        } else {
                            issue_tile(cta, i, sb + ist * STAGE, bar_full + 8 * ist, p, pol, &tm_wq, &tm_wo, &tm_wg, &tm_wu, &tm_wd);
                        }
                        i++;
                        if (++ist == NST) { ist = 0; iph ^= 1; }
                    }
                }
            }
        } else if (tid == 64 && is_attn) {
            uint32_t it = 0;
            while (!lds32(sb + OFF_PACE + 4) && ++it < kSpinLimit) {
                sts32(sb + OFF_PACE, load_relaxed(&g_landed));
                __nanosleep(200);
            }
        } else if (tid == 32 && is_attn) {
            uint32_t it = 0;
            do {
                __nanosleep(4000);
            } while (load_relaxed(&g_stage) < 2 * kGluCtas && ++it < kSpinLimit);
            fence_gpu();
            mbar_arrive(bar_gate);
            red_inc(&g_stage, kStageWrap);
        }
    } else {
        asm volatile("setmaxnreg.inc.sync.aligned.u32 232;");
        const int g = lane >> 2, t = lane & 3, mi = lane >> 3, r = lane & 7;
        Ring ring{bar_full, bar_empty, sb, 0u, 0u};

        if (ln_warp) {
            const uint32_t w[8] = {xv0.x, xv0.y, xv0.z, xv0.w, xv1.x, xv1.y, xv1.z, xv1.w};
            float f[16];
            float sum = 0.f;
#pragma unroll
            for (int i = 0; i < 8; i++) {
                f[2 * i] = bf_lo(w[i]);
                f[2 * i + 1] = bf_hi(w[i]);
                sum += f[2 * i] + f[2 * i + 1];
            }
#pragma unroll
            for (int o = 16; o; o >>= 1) sum += __shfl_xor_sync(0xffffffffu, sum, o);
            const float mean = sum * (1.0f / kD);
            float var = 0.f;
#pragma unroll
            for (int i = 0; i < 16; i++) var += (f[i] - mean) * (f[i] - mean);
#pragma unroll
            for (int o = 16; o; o >>= 1) var += __shfl_xor_sync(0xffffffffu, var, o);
            const float mb = bf16r(mean);
            const float den = bf16r(fsqrt(bf16r(bf16r(var * (1.0f / kD)) + 1e-5f)));
            uint32_t o8[8];
#pragma unroll
            for (int i = 0; i < 8; i++) o8[i] = pack_bf16(fdiv(bf16r(f[2 * i] - mb), den), fdiv(bf16r(f[2 * i + 1] - mb), den));
            const uint32_t xr = sb + OFF_XN + ln_row * XN_STRIDE + lane * 16;
            sts128(xr, o8[0], o8[1], o8[2], o8[3]);
            sts128(xr + 512, o8[4], o8[5], o8[6], o8[7]);
            if (is_attn) {
                sts128(sb + OFF_XR + ln_row * 1024 + lane * 16, w[0], w[1], w[2], w[3]);
                sts128(sb + OFF_XR + ln_row * 1024 + 512 + lane * 16, w[4], w[5], w[6], w[7]);
            }
        }
        bar_consumers();
        if (tid == 128) TS(2);

        if (is_attn) {
            {
                float qa[4] = {0.f, 0.f, 0.f, 0.f}, qb[4] = {0.f, 0.f, 0.f, 0.f};
                const uint32_t aoff = (cw >> 2) * 16384 + ((mi >> 1) * 8 + r) * 128 + (((2 * (cw & 3) + (mi & 1)) ^ r) << 4);
                const uint32_t boff = sb + OFF_XN + (r & 1) * XN_STRIDE + mi * 16;
#pragma unroll 1
                for (int i = 0; i < 4; i++) {
                    const uint32_t base = ring.acquire() + aoff;
#pragma unroll
                    for (int s2 = 0; s2 < 4; s2++) {
                        uint32_t b[4], a0[4], a1[4];
                        ldsm4(b, boff + i * 256 + s2 * 64);
                        ldsm4t(a0, base + s2 * 4096);
                        ldsm4t(a1, base + s2 * 4096 + 2048);
                        mma16816(qa, a0, b[0], b[1]);
                        mma16816(qb, a1, b[2], b[3]);
                    }
                    ring.release(lane);
                }
                if (t == 0) {
                    const uint32_t qd = sb + OFF_QS + (16 * cw + g) * 2;
                    sts16(qd, qa[0] + qb[0]);
                    sts16(qd + 256, qa[1] + qb[1]);
                    sts16(qd + 16, qa[2] + qb[2]);
                    sts16(qd + 256 + 16, qa[3] + qb[3]);
                }
                bar_consumers();
                if (tid == 128) TS(3);
            }

            uint32_t wo[8][4][4];
            const bool diag = t == (g >> 1);
            const uint32_t sel0 = diag ? ((g & 1) ? 0x1044u : 0x4410u) : 0x4444u;
            const uint32_t sel1 = diag ? ((g & 1) ? 0x3244u : 0x4432u) : 0x4444u;
            const uint32_t sc = sb + OFF_SC + cw * 1024;
            const uint32_t red = sb + OFF_RED;
            const uint32_t koff = (16 * cw + (mi & 1) * 8 + r) * 256 + (((mi >> 1) ^ r) << 4);
            const uint32_t voff = (16 * cw + (mi >> 1) * 8 + r) * 256 + (((mi & 1) ^ r) << 4);

#pragma unroll 1
            for (int bb = 0; bb < 2; bb++) {
                float mx = -INFINITY;
                {
                    uint32_t bq[8][2];
#pragma unroll
                    for (int j = 0; j < 8; j++) {
                        bq[j][0] = lds32(sb + OFF_QS + bb * 256 + (((2 * j) ^ g) << 4) + t * 4);
                        bq[j][1] = lds32(sb + OFF_QS + bb * 256 + (((2 * j + 1) ^ g) << 4) + t * 4);
                    }
#pragma unroll 1
                    for (int tile = 0; tile < TILES; tile++) {
                        if (bb == 0 && tile == WO_POS) {
#pragma unroll
                            for (int i = 0; i < 4; i++) {
                                const uint32_t base = ring.acquire() + cw * 4096;
#pragma unroll
                                for (int ks = 0; ks < 2; ks++)
#pragma unroll
                                    for (int mt = 0; mt < 4; mt++)
                                        ldsm4t(wo[2 * i + ks][mt],
                                               base + (16 * ks + (mi >> 1) * 8 + r) * 128 + (((2 * mt + (mi & 1)) ^ r) << 4));
                                ring.release(lane);
                            }
                        }
                        const uint32_t base = ring.acquire();
                        float c0[4] = {0.f, 0.f, 0.f, 0.f}, c1[4] = {0.f, 0.f, 0.f, 0.f};
#pragma unroll
                        for (int j = 0; j < 8; j += 2) {
                            uint32_t a0[4], a1[4];
                            ldsm4(a0, base + (koff ^ (j << 5)));
                            ldsm4(a1, base + (koff ^ ((j + 1) << 5)));
                            mma16816(c0, a0, bq[j][0], bq[j][1]);
                            mma16816(c1, a1, bq[j + 1][0], bq[j + 1][1]);
                        }
                        ring.release(lane);
                        const float d0 = (g & 1) ? c0[1] + c1[1] : c0[0] + c1[0];
                        const float d1 = (g & 1) ? c0[3] + c1[3] : c0[2] + c1[2];
                        const float scale = 0.08838834764831845f;
                        const uint32_t sp = pack_bf16(bf16r(d0) * scale, bf16r(d1) * scale);
                        if (diag) {
                            mx = fmaxf(mx, fmaxf(bf_lo(sp), bf_hi(sp)));
                            sts32(sc + (tile * 8 + g) * 4, sp);
                        }
                    }
                }
                if (tid == 128) TS(4 + 5 * bb);
                {
#pragma unroll
                    for (int o = 16; o; o >>= 1) mx = fmaxf(mx, __shfl_xor_sync(0xffffffffu, mx, o));
                    if (lane == 0) sts32(red + cw * 4, __float_as_uint(mx));
                    bar_consumers();
                    const uint4 m0 = lds128(red), m1 = lds128(red + 16);
                    mx = fmaxf(fmaxf(fmaxf(__uint_as_float(m0.x), __uint_as_float(m0.y)), fmaxf(__uint_as_float(m0.z), __uint_as_float(m0.w))),
                               fmaxf(fmaxf(__uint_as_float(m1.x), __uint_as_float(m1.y)), fmaxf(__uint_as_float(m1.z), __uint_as_float(m1.w))));
                    const uint4 s0 = lds128(sc + lane * 16), s1 = lds128(sc + 512 + lane * 16);
                    const uint32_t w[8] = {s0.x, s0.y, s0.z, s0.w, s1.x, s1.y, s1.z, s1.w};
                    float e[16];
                    float sum = 0.f;
                    const float log2e = 1.4426950408889634f;
#pragma unroll
                    for (int i = 0; i < 8; i++) {
                        e[2 * i] = exp2f((bf_lo(w[i]) - mx) * log2e);
                        e[2 * i + 1] = exp2f((bf_hi(w[i]) - mx) * log2e);
                        sum += e[2 * i] + e[2 * i + 1];
                    }
#pragma unroll
                    for (int o = 16; o; o >>= 1) sum += __shfl_xor_sync(0xffffffffu, sum, o);
                    if (lane == 0) sts32(red + 32 + cw * 4, __float_as_uint(sum));
                    bar_consumers();
                    const uint4 t0 = lds128(red + 32), t1 = lds128(red + 48);
                    const float tot = ((__uint_as_float(t0.x) + __uint_as_float(t0.y)) + (__uint_as_float(t0.z) + __uint_as_float(t0.w))) +
                                      ((__uint_as_float(t1.x) + __uint_as_float(t1.y)) + (__uint_as_float(t1.z) + __uint_as_float(t1.w)));
                    const float inv = fdiv(1.0f, tot);
                    sts128(sc + lane * 16, pack_bf16(e[0] * inv, e[1] * inv), pack_bf16(e[2] * inv, e[3] * inv),
                           pack_bf16(e[4] * inv, e[5] * inv), pack_bf16(e[6] * inv, e[7] * inv));
                    sts128(sc + 512 + lane * 16, pack_bf16(e[8] * inv, e[9] * inv), pack_bf16(e[10] * inv, e[11] * inv),
                           pack_bf16(e[12] * inv, e[13] * inv), pack_bf16(e[14] * inv, e[15] * inv));
                    __syncwarp();
                }
                if (tid == 128) TS(5 + 5 * bb);
                const int col = 64 * cw + 16 * t + g;
                float4* slot = g_acc + ((cta & 3) + 4 * bb) * 256 + cw * 32 + lane;
                unsigned short* outp = reinterpret_cast<unsigned short*>(p.out) + ((cta & 3) + 4 * bb) * kD + col;
                asm volatile("" : "+l"(slot), "+l"(outp));
                float acc[8][4];
#pragma unroll
                for (int j = 0; j < 8; j++) acc[j][0] = acc[j][1] = acc[j][2] = acc[j][3] = 0.f;
#pragma unroll 1
                for (int tile = 0; tile < TILES; tile++) {
                    const uint32_t pw = lds32(sc + (tile * 8 + g) * 4);
                    const uint32_t b0 = __byte_perm(pw, 0, sel0), b1 = __byte_perm(pw, 0, sel1);
                    if (tile == TILES - 2) mbar_wait(bar_gate, 0);
                    const bool last = bb == 1 && tile == TILES - 1;
                    mbar_wait(last ? bar_last + 8 * (cw * LAST_SPLIT / 8) : ring.full0 + 8 * ring.st, last ? 0 : ring.ph);
                    const uint32_t base = ring.data0 + ring.st * STAGE;
                    if (tid == 128 + 224 && tile == TILES - 1) TS(6 + 5 * bb);
#pragma unroll
                    for (int j = 0; j < 8; j++) {
                        uint32_t a[4];
                        ldsm4t(a, base + (voff ^ (j << 5)));
                        mma16816(acc[j], a, b0, b1);
                    }
                    ring.release(lane);
                }
                {
                    float ev[8], od[8];
#pragma unroll
                    for (int j = 0; j < 8; j++) {
                        ev[j] = acc[j][0] + acc[j][3];
                        od[j] = acc[j][1] + acc[j][2];
                    }
#pragma unroll
                    for (int j = 0; j < 8; j += 2) {
                        ev[j] += __shfl_xor_sync(0xffffffffu, ev[j + 1], 1);
                        od[j] += __shfl_xor_sync(0xffffffffu, od[j + 1], 1);
                    }
#pragma unroll
                    for (int j = 0; j < 8; j += 4) {
                        ev[j] += __shfl_xor_sync(0xffffffffu, ev[j + 2], 2);
                        od[j] += __shfl_xor_sync(0xffffffffu, od[j + 2], 2);
                    }
                    const uint32_t od_addr = sb + OFF_OB + cw * OB_STRIDE + (16 * t + g) * 2;
                    sts16(od_addr, ev[0]);
                    sts16(od_addr + 16, od[0]);
                    sts16(od_addr + 128, ev[4]);
                    sts16(od_addr + 144, od[4]);
                }
                bar_consumers();
                {
                    float pc[4][4];
#pragma unroll
                    for (int mt = 0; mt < 4; mt++) pc[mt][0] = pc[mt][1] = pc[mt][2] = pc[mt][3] = 0.f;
#pragma unroll
                    for (int s2 = 0; s2 < 4; s2++) {
                        uint32_t b[4];
                        ldsm4(b, sb + OFF_OB + r * OB_STRIDE + s2 * 64 + mi * 16);
#pragma unroll
                        for (int mt = 0; mt < 4; mt++) mma16816(pc[mt], wo[2 * s2][mt], b[0], b[1]);
#pragma unroll
                        for (int mt = 0; mt < 4; mt++) mma16816(pc[mt], wo[2 * s2 + 1][mt], b[2], b[3]);
                    }
                    float lo[4], hi[4];
#pragma unroll
                    for (int mt = 0; mt < 4; mt++) {
                        lo[mt] = pc[mt][0] + pc[mt][1];
                        hi[mt] = pc[mt][2] + pc[mt][3];
                    }
                    const bool t1 = t & 1, t2 = t & 2;
                    const float yl0 = (t1 ? lo[1] : lo[0]) + __shfl_xor_sync(0xffffffffu, t1 ? lo[0] : lo[1], 1);
                    const float yl1 = (t1 ? lo[3] : lo[2]) + __shfl_xor_sync(0xffffffffu, t1 ? lo[2] : lo[3], 1);
                    const float yh0 = (t1 ? hi[1] : hi[0]) + __shfl_xor_sync(0xffffffffu, t1 ? hi[0] : hi[1], 1);
                    const float yh1 = (t1 ? hi[3] : hi[2]) + __shfl_xor_sync(0xffffffffu, t1 ? hi[2] : hi[3], 1);
                    const float zl = (t2 ? yl1 : yl0) + __shfl_xor_sync(0xffffffffu, t2 ? yl0 : yl1, 2);
                    const float zh = (t2 ? yh1 : yh0) + __shfl_xor_sync(0xffffffffu, t2 ? yh0 : yh1, 2);
                    if (tid == 128) TS(7 + 5 * bb);
                    out_arrive(slot, zl, zh, sb + OFF_XR + bb * 1024 + col * 2, outp);
                    if (tid == 128) TS(8 + 5 * bb);
                }
            }
        } else {
            float ga[4][4], ua[4][4];
#pragma unroll
            for (int mt = 0; mt < 4; mt++)
#pragma unroll
                for (int i = 0; i < 4; i++) ga[mt][i] = ua[mt][i] = 0.f;
            const uint32_t xb = sb + OFF_XN + r * XN_STRIDE + mi * 16;
#pragma unroll 1
            for (int i = 0; i < 16; i++) {
                const uint32_t base = ring.acquire();
                if (cw < 7) gemm_block32(ga, base + cw * 4096, xb + i * 64, lane);
                ring.release(lane);
            }
#pragma unroll 1
            for (int i = 0; i < 16; i++) {
                const uint32_t base = ring.acquire();
                if (cw < 7) gemm_block32(ua, base + cw * 4096, xb + i * 64, lane);
                ring.release(lane);
            }
            const uint32_t hs = sb + OFF_SC;
            if (cw < 7) {
#pragma unroll
                for (int mt = 0; mt < 4; mt++)
#pragma unroll
                    for (int i = 0; i < 4; i++)
                        sts16(hs + (2 * t + (i & 1)) * HS_STRIDE + (64 * cw + 16 * mt + g + (i >> 1) * 8) * 2,
                              bf16r(ga[mt][i]) * bf16r(ua[mt][i]));
            }
            bar_consumers();
#pragma unroll
            for (int mt = 0; mt < 4; mt++)
#pragma unroll
                for (int i = 0; i < 4; i++) ga[mt][i] = 0.f;
#pragma unroll 1
            for (int i = 0; i < 14; i++) {
                const uint32_t base = ring.acquire();
                gemm_block32(ga, base + cw * 4096, hs + r * HS_STRIDE + mi * 16 + i * 64, lane);
                ring.release(lane);
            }
            const int j = cta - kAttnCtas;
#pragma unroll
            for (int e = 0; e < 2; e++) {
                float4* dst = reinterpret_cast<float4*>(g_glu + (j * kB + 2 * t + e) * 256 + cw * 32 + g * 4);
                dst[0] = make_float4(ga[0][e], ga[0][2 + e], ga[1][e], ga[1][2 + e]);
                dst[1] = make_float4(ga[2][e], ga[2][2 + e], ga[3][e], ga[3][2 + e]);
            }
            bar_consumers();
            if (tid == 128) {
                fence_gpu();
                red_inc(&g_stage, kStageWrap);
                uint32_t it = 0;
                while (load_relaxed(&g_stage) < kGluCtas && ++it < kSpinLimit) __nanosleep(200);
                fence_gpu();
            }
            bar_consumers();
            const int si = j * 512 + (tid - 128) * 2;
            float4 d = make_float4(0.f, 0.f, 0.f, 0.f);
#pragma unroll
            for (int k = 0; k < kGluCtas; k++) {
                const float4 v = __ldcg(reinterpret_cast<const float4*>(g_glu + k * kB * 256 + si));
                d.x += v.x; d.y += v.y; d.z += v.z; d.w += v.w;
            }
            const float dd[4] = {bf16r(d.x), bf16r(d.y), bf16r(d.z), bf16r(d.w)};
            float gb[4];
#pragma unroll
            for (int k = 0; k < 4; k++) gb[k] = (float)(pack_bf16(fdiv(dd[k], 1.0f + expf(-dd[k])), 0.f) & 0xffffu);
            g_acc[si] = make_float4(0.f, 0.f, gb[0], gb[1]);
            g_acc[si + 1] = make_float4(0.f, 0.f, gb[2], gb[3]);
            bar_consumers();
            if (tid == 128) {
                fence_gpu();
                red_inc(&g_stage, kStageWrap);
            }
            if (tid == 128) TS(15);
        }
    }
}

typedef CUresult (*EncodeFn)(CUtensorMap*, CUtensorMapDataType, cuuint32_t, void*, const cuuint64_t*, const cuuint64_t*,
                             const cuuint32_t*, const cuuint32_t*, CUtensorMapInterleave, CUtensorMapSwizzle,
                             CUtensorMapL2promotion, CUtensorMapFloatOOBfill);

void encode_weight(EncodeFn fn, CUtensorMap* m, void* ptr, int rows, int cols, int box_rows, int box_grps) {
    cuuint64_t dims[3] = {64, (cuuint64_t)rows, (cuuint64_t)(cols / 64)};
    cuuint64_t strides[2] = {(cuuint64_t)cols * 2, 128};
    cuuint32_t box[3] = {64, (cuuint32_t)box_rows, (cuuint32_t)box_grps};
    cuuint32_t es[3] = {1, 1, 1};
    fn(m, CU_TENSOR_MAP_DATA_TYPE_BFLOAT16, 3, ptr, dims, strides, box, es, CU_TENSOR_MAP_INTERLEAVE_NONE,
       CU_TENSOR_MAP_SWIZZLE_128B, CU_TENSOR_MAP_L2_PROMOTION_NONE, CU_TENSOR_MAP_FLOAT_OOB_FILL_NONE);
}

}

extern "C" void kernel_launch(void* const* d_in, const int* in_sizes, int n_in, void* d_out, int out_size) {
    static EncodeFn encode = nullptr;
    if (!encode) {
        void* fn = nullptr;
        cudaDriverEntryPointQueryResult qr;
        cudaGetDriverEntryPoint("cuTensorMapEncodeTiled", &fn, cudaEnableDefault, &qr);
        encode = (EncodeFn)fn;
        cudaFuncSetAttribute(fused_decode_kernel, cudaFuncAttributeMaxDynamicSharedMemorySize, SMEM_BYTES);
    }
    Params p;
    p.x = (const __nv_bfloat16*)d_in[0];
    p.k = (const char*)d_in[1];
    p.v = (const char*)d_in[2];
    p.out = (__nv_bfloat16*)d_out;
    CUtensorMap tm_wq, tm_wo, tm_wg, tm_wu, tm_wd;
    encode_weight(encode, &tm_wq, d_in[3], kD, kH * kDh, 128, 2);
    encode_weight(encode, &tm_wo, d_in[4], kH * kDh, kD, 32, 8);
    encode_weight(encode, &tm_wg, d_in[6], kD, kF, 32, 7);
    encode_weight(encode, &tm_wu, d_in[7], kD, kF, 32, 7);
    encode_weight(encode, &tm_wd, d_in[8], kF, kD, 32, 8);
    fused_decode_kernel<<<kGrid, kThreads, SMEM_BYTES>>>(p, tm_wq, tm_wo, tm_wg, tm_wu, tm_wd);
}
```

```cpp
#include <cuda_runtime.h>
#include <cuda_bf16.h>
#include <cuda.h>
#include <stdint.h>

namespace {

constexpr int kB = 8, kD = 512, kH = 32, kSk = 4096, kDh = 128, kF = 1792;
constexpr int kAttnCtas = 128, kGluCtas = 4, kGrid = kAttnCtas + kGluCtas;
constexpr int kThreads = 384;

constexpr int NST = 6;
constexpr int STAGE = 32768;
constexpr int TILES = kSk / 128;
constexpr int WO_POS = 2;
constexpr int kAttnTiles = 8 + 4 * TILES;
constexpr int kGluTiles = 46;

constexpr int kFree1 = 12, kWin1 = 6, kFree2 = 16, kWin2 = 3;
constexpr int kPaceWin2x = 6, kPaceGain2x = 3;

constexpr int XN_STRIDE = 1040;
constexpr int HS_STRIDE = 912;
constexpr int OB_STRIDE = 272;

constexpr int OFF_SC = NST * STAGE;
constexpr int OFF_XN = OFF_SC + 8192;
constexpr int OFF_XR = OFF_XN + 8 * XN_STRIDE;
constexpr int OFF_QS = OFF_XR + 2 * 1024;
constexpr int OFF_OB = OFF_QS + 512;
constexpr int OFF_RED = OFF_OB + 8 * OB_STRIDE;
constexpr int OFF_BAR = OFF_RED + 64;
constexpr int OFF_PACE = OFF_BAR + 8 * (2 * NST + 1 + 16);
constexpr int SMEM_BYTES = OFF_PACE + 8;

constexpr uint32_t kTryLimit = 1u << 13;
constexpr uint32_t kSpinLimit = 1u << 21;
constexpr uint32_t kSleepLimit = 1u << 17;
constexpr uint32_t kPaceLimit = 1u << 15;

__device__ __align__(1024) float4 g_acc[kB * 256];
__device__ __align__(1024) float2 g_glu[kGluCtas * kB * 256];
__device__ __align__(1024) uint32_t g_sync[128];
constexpr uint32_t kLandedWrap = kAttnCtas * (kAttnTiles - 1) - 1;
constexpr uint32_t kStageWrap = 2 * kGluCtas + kAttnCtas - 1;

__device__ __forceinline__ uint32_t smem_u32(const void* p) { return (uint32_t)__cvta_generic_to_shared(p); }

__device__ __forceinline__ void mbar_init(uint32_t bar, uint32_t cnt) {
    asm volatile("mbarrier.init.shared.b64 [%0], %1;" ::"r"(bar), "r"(cnt) : "memory");
}
__device__ __forceinline__ void mbar_expect(uint32_t bar, uint32_t bytes) {
    asm volatile("mbarrier.arrive.expect_tx.shared.b64 _, [%0], %1;" ::"r"(bar), "r"(bytes) : "memory");
}
__device__ __forceinline__ void mbar_arrive(uint32_t bar) {
    asm volatile("mbarrier.arrive.shared.b64 _, [%0];" ::"r"(bar) : "memory");
}
__device__ __forceinline__ void mbar_wait(uint32_t bar, uint32_t parity) {
    uint32_t ok, it = 0;
    do {
        asm volatile("{.reg .pred p; mbarrier.try_wait.parity.shared.b64 p, [%1], %2; selp.u32 %0, 1, 0, p;}"
                     : "=r"(ok) : "r"(bar), "r"(parity) : "memory");
        if (++it > kTryLimit) break;
    } while (!ok);
}
__device__ __forceinline__ bool mbar_test(uint32_t bar, uint32_t parity) {
    uint32_t ok;
    asm volatile("{.reg .pred p; mbarrier.test_wait.parity.shared.b64 p, [%1], %2; selp.u32 %0, 1, 0, p;}"
                 : "=r"(ok) : "r"(bar), "r"(parity) : "memory");
    return ok;
}
__device__ __forceinline__ void bulk_load(uint32_t dst, const void* src, uint32_t bytes, uint32_t bar, uint64_t pol) {
    asm volatile("cp.async.bulk.shared::cluster.global.mbarrier::complete_tx::bytes.L2::cache_hint [%0], [%1], %2, [%3], %4;"
                 ::"r"(dst), "l"(src), "r"(bytes), "r"(bar), "l"(pol) : "memory");
}
__device__ __forceinline__ void tma_load3(uint32_t dst, const CUtensorMap* m, int row, int grp, uint32_t bar) {
    asm volatile("cp.async.bulk.tensor.3d.shared::cluster.global.mbarrier::complete_tx::bytes [%0], [%1, {%3, %4, %5}], [%2];"
                 ::"r"(dst), "l"(m), "r"(bar), "r"(0), "r"(row), "r"(grp) : "memory");
}
__device__ __forceinline__ void ldsm4(uint32_t (&r)[4], uint32_t addr) {
    asm volatile("ldmatrix.sync.aligned.m8n8.x4.shared.b16 {%0,%1,%2,%3}, [%4];"
                 : "=r"(r[0]), "=r"(r[1]), "=r"(r[2]), "=r"(r[3]) : "r"(addr) : "memory");
}
__device__ __forceinline__ void ldsm4t(uint32_t (&r)[4], uint32_t addr) {
    asm volatile("ldmatrix.sync.aligned.m8n8.x4.trans.shared.b16 {%0,%1,%2,%3}, [%4];"
                 : "=r"(r[0]), "=r"(r[1]), "=r"(r[2]), "=r"(r[3]) : "r"(addr) : "memory");
}
__device__ __forceinline__ void mma16816(float (&c)[4], const uint32_t (&a)[4], uint32_t b0, uint32_t b1) {
    asm volatile("mma.sync.aligned.m16n8k16.row.col.f32.bf16.bf16.f32 {%0,%1,%2,%3}, {%4,%5,%6,%7}, {%8,%9}, {%0,%1,%2,%3};"
                 : "+f"(c[0]), "+f"(c[1]), "+f"(c[2]), "+f"(c[3])
                 : "r"(a[0]), "r"(a[1]), "r"(a[2]), "r"(a[3]), "r"(b0), "r"(b1));
}
__device__ __forceinline__ void bar_consumers() { asm volatile("bar.sync 1, 256;" ::: "memory"); }

__device__ __forceinline__ uint32_t pack_bf16(float lo, float hi) {
    uint32_t r;
    asm("cvt.rn.bf16x2.f32 %0, %1, %2;" : "=r"(r) : "f"(hi), "f"(lo));
    return r;
}
__device__ __forceinline__ float bf16r(float x) { return __uint_as_float(pack_bf16(0.f, x)); }
__device__ __forceinline__ float fdiv(float a, float b) {
    float r;
    asm("div.full.f32 %0, %1, %2;" : "=f"(r) : "f"(a), "f"(b));
    return r;
}
__device__ __forceinline__ float fsqrt(float a) {
    float r;
    asm("sqrt.approx.f32 %0, %1;" : "=f"(r) : "f"(a));
    return r;
}
__device__ __forceinline__ float bf_lo(uint32_t v) { return __uint_as_float(v << 16); }
__device__ __forceinline__ float bf_hi(uint32_t v) { return __uint_as_float(v & 0xffff0000u); }

__device__ __forceinline__ void sts16(uint32_t addr, float v) {
    asm volatile("st.shared.b16 [%0], %1;" ::"r"(addr), "h"((unsigned short)pack_bf16(v, 0.f)) : "memory");
}
__device__ __forceinline__ void sts32(uint32_t addr, uint32_t v) {
    asm volatile("st.shared.b32 [%0], %1;" ::"r"(addr), "r"(v) : "memory");
}
__device__ __forceinline__ void sts128(uint32_t addr, uint32_t a, uint32_t b, uint32_t c, uint32_t d) {
    asm volatile("st.shared.v4.b32 [%0], {%1,%2,%3,%4};" ::"r"(addr), "r"(a), "r"(b), "r"(c), "r"(d) : "memory");
}
__device__ __forceinline__ uint32_t lds32(uint32_t addr) {
    uint32_t v;
    asm volatile("ld.shared.b32 %0, [%1];" : "=r"(v) : "r"(addr) : "memory");
    return v;
}
__device__ __forceinline__ uint32_t lds32_volatile(uint32_t addr) {
    uint32_t v;
    asm volatile("ld.volatile.shared.b32 %0, [%1];" : "=r"(v) : "r"(addr) : "memory");
    return v;
}
__device__ __forceinline__ void sts32_volatile(uint32_t addr, uint32_t v) {
    asm volatile("st.volatile.shared.b32 [%0], %1;" ::"r"(addr), "r"(v) : "memory");
}
__device__ __forceinline__ uint4 lds128(uint32_t addr) {
    uint4 v;
    asm volatile("ld.shared.v4.b32 {%0,%1,%2,%3}, [%4];" : "=r"(v.x), "=r"(v.y), "=r"(v.z), "=r"(v.w) : "r"(addr) : "memory");
    return v;
}
__device__ __forceinline__ uint32_t lds16(uint32_t addr) {
    unsigned short v;
    asm volatile("ld.shared.b16 %0, [%1];" : "=h"(v) : "r"(addr) : "memory");
    return v;
}
__device__ __forceinline__ void out_arrive(float4* slot, float s0, float s1, float x0, float x1, unsigned short* outp) {
    float4 o;
    asm volatile("atom.relaxed.gpu.global.add.v4.f32 {%0,%1,%2,%3}, [%4], {%5,%6,%7,%8};"
                 : "=f"(o.x), "=f"(o.y), "=f"(o.z), "=f"(o.w)
                 : "l"(slot), "f"(s0), "f"(s1), "f"(65536.f), "f"(0.f) : "memory");
    const float g0 = __uint_as_float(__float_as_uint(o.z + 8388608.f) << 16);
    const float g1 = __uint_as_float(__float_as_uint(o.w + 8388608.f) << 16);
    const uint32_t r0 = pack_bf16(x0 + bf16r(bf16r(o.x + s0) * g0), 0.f);
    const uint32_t r1 = pack_bf16(x1 + bf16r(bf16r(o.y + s1) * g1), 0.f);
    asm volatile("{.reg .pred p; setp.ge.f32 p, %3, %4;\n"
                 "@p st.global.b16 [%0], %1;\n"
                 "@p st.global.b16 [%0+16], %2;}"
                 ::"l"(outp), "h"((unsigned short)r0), "h"((unsigned short)r1), "f"(o.z), "f"(65536.f * (kH - 1)) : "memory");
}
__device__ __forceinline__ void fence_gpu() { asm volatile("fence.acq_rel.gpu;" ::: "memory"); }
__device__ __forceinline__ uint32_t load_relaxed(const uint32_t* p) {
    uint32_t v;
    asm volatile("ld.relaxed.gpu.global.u32 %0, [%1];" : "=r"(v) : "l"(p) : "memory");
    return v;
}
__device__ __forceinline__ void red_inc(uint32_t* p, uint32_t limit) {
    asm volatile("red.relaxed.gpu.global.inc.u32 [%0], %1;" ::"l"(p), "r"(limit) : "memory");
}

struct Ring {
    uint32_t full0, empty0, data0;
    uint32_t st, ph;
    __device__ __forceinline__ uint32_t acquire() {
        mbar_wait(full0 + 8 * st, ph);
        return data0 + st * STAGE;
    }
    __device__ __forceinline__ void release(int lane) {
        __syncwarp();
        if (lane == 0) mbar_arrive(empty0 + 8 * st);
        if (++st == NST) { st = 0; ph ^= 1; }
    }
};

struct Params {
    const __nv_bfloat16* x;
    const char* k;
    const char* v;
    __nv_bfloat16* out;
};

__device__ __forceinline__ void issue_tile(int cta, int i, uint32_t dst, uint32_t bar, const Params& p, uint64_t pol,
                                           const CUtensorMap* tm_wo, const CUtensorMap* tm_wg, const CUtensorMap* tm_wu,
                                           const CUtensorMap* tm_wd) {
    static_assert(4 + WO_POS == NST, "the prologue issues the tiles ahead of wo");
    if (cta < kAttnCtas) {
        const int h = cta >> 2;
        mbar_expect(bar, STAGE);
        if (i < NST + 4) {
            tma_load3(dst, tm_wo, 128 * h + 32 * (i - NST), 0, bar);
        } else {
            const int c = i - 8;
            const int bh = ((cta & 3) + 4 * (c >> 6)) * kH + h;
            const char* base = (c & 32) ? p.v : p.k;
            bulk_load(dst, base + ((size_t)bh << 20) + ((size_t)(c & 31) << 15), STAGE, bar, pol);
        }
    } else {
        const int j = cta - kAttnCtas;
        if (i < 32) {
            mbar_expect(bar, 7 * 4096);
            tma_load3(dst, i < 16 ? tm_wg : tm_wu, 32 * (i & 15), 7 * j, bar);
        } else {
            mbar_expect(bar, STAGE);
            tma_load3(dst, tm_wd, 448 * j + 32 * (i - 32), 0, bar);
        }
    }
}

__device__ __forceinline__ void gemm_block32(float (&acc)[4][4], uint32_t wbase, uint32_t baddr, int lane) {
    const int mi = lane >> 3, r = lane & 7;
    uint32_t b[4];
    ldsm4(b, baddr);
#pragma unroll
    for (int ks = 0; ks < 2; ks++) {
#pragma unroll
        for (int mt = 0; mt < 4; mt++) {
            uint32_t a[4];
            ldsm4t(a, wbase + (16 * ks + (mi >> 1) * 8 + r) * 128 + (((2 * mt + (mi & 1)) ^ r) << 4));
            mma16816(acc[mt], a, b[2 * ks], b[2 * ks + 1]);
        }
    }
}

template <bool kResident>
__global__ void __launch_bounds__(kThreads, 1)
fused_decode_kernel(const Params p,
                    const __grid_constant__ CUtensorMap tm_wq, const __grid_constant__ CUtensorMap tm_wo,
                    const __grid_constant__ CUtensorMap tm_wg, const __grid_constant__ CUtensorMap tm_wu,
                    const __grid_constant__ CUtensorMap tm_wd) {
    extern __shared__ __align__(1024) char smem[];
    const uint32_t sb = smem_u32(smem);
    const uint32_t bar_full = sb + OFF_BAR, bar_empty = bar_full + 8 * NST;
    const uint32_t bar_gate = bar_empty + 8 * NST, bar_last = bar_gate + 8;
    const int tid = threadIdx.x, warp = tid >> 5, lane = tid & 31;
    const int blk33 = blockIdx.x / 33;
    const bool is_attn = kResident ? blockIdx.x - blk33 * 33 != 32 : blockIdx.x >= kGluCtas;
    const int cta = kResident ? (is_attn ? blockIdx.x - blk33 : kAttnCtas + blk33)
                              : (is_attn ? blockIdx.x - kGluCtas : kAttnCtas + blockIdx.x);

    uint64_t pol;
    asm volatile("createpolicy.fractional.L2::evict_first.b64 %0, 1.0;" : "=l"(pol));
    uint4 xv0 = make_uint4(0, 0, 0, 0), xv1 = xv0;
    const int cw = warp - 4;
    const bool ln_warp = is_attn ? cw >= 6 : cw >= 0;
    const int ln_row = is_attn ? cw - 6 : cw;
    const char* k0 = p.k + ((size_t)((cta & 3) * kH + (cta >> 2)) << 20);
    if (tid == 0) {
        mbar_init(bar_full + 8 * 4, 1);
        if (is_attn) {
            asm volatile("fence.mbarrier_init.release.cluster;" ::: "memory");
            mbar_expect(bar_full + 8 * 4, STAGE);
            bulk_load(sb + 4 * STAGE, k0, STAGE, bar_full + 8 * 4, pol);
        }
#pragma unroll
        for (int i = 0; i < NST; i++)
            if (i != 4) mbar_init(bar_full + 8 * i, 1);
        asm volatile("fence.mbarrier_init.release.cluster;" ::: "memory");
        const CUtensorMap* tm0 = is_attn ? &tm_wq : &tm_wg;
        const int rstep = is_attn ? 128 : 32, grp = is_attn ? 2 * (cta >> 2) : 7 * (cta - kAttnCtas);
        const uint32_t bytes = is_attn ? STAGE : 7 * 4096;
#pragma unroll
        for (int i = 0; i < 4; i++) {
            mbar_expect(bar_full + 8 * i, bytes);
            tma_load3(sb + i * STAGE, tm0, rstep * i, grp, bar_full + 8 * i);
        }
        if (is_attn) {
            mbar_expect(bar_full + 8 * 5, STAGE);
            bulk_load(sb + 5 * STAGE, k0 + STAGE, STAGE, bar_full + 8 * 5, pol);
        } else {
#pragma unroll
            for (int i = 4; i < NST; i++) {
                mbar_expect(bar_full + 8 * i, bytes);
                tma_load3(sb + i * STAGE, tm0, rstep * i, grp, bar_full + 8 * i);
            }
        }
    }
    if (ln_warp) {
        const uint4* xr = reinterpret_cast<const uint4*>(p.x + (is_attn ? (cta & 3) + 4 * ln_row : ln_row) * kD);
        xv0 = __ldg(xr + lane);
        xv1 = __ldg(xr + 32 + lane);
    }
    if (tid == 6 * 32) {
#pragma unroll
        for (int i = 0; i < NST; i++) mbar_init(bar_empty + 8 * i, 8);
        mbar_init(bar_gate, 1);
#pragma unroll
        for (int i = 0; i < 16; i++) mbar_init(bar_last + 8 * i, 1);
        sts32(sb + OFF_PACE, 0);
        sts32(sb + OFF_PACE + 4, 0);
        asm volatile("fence.mbarrier_init.release.cluster;" ::: "memory");
    }
    __syncthreads();

    if (warp < 4) {
        asm volatile("setmaxnreg.dec.sync.aligned.u32 40;");
        if (tid == 0) {
            const int n = is_attn ? kAttnTiles : kGluTiles;
            const int ntrack = is_attn ? n - 1 : 0;
            int i = NST, c = 0, part = 0;
            uint32_t ist = 0, iph = 0, cst = 0, cph = 0, idle = 0;
            bool paced = kResident && is_attn;
            while ((i < n || c < ntrack) && ++idle < kSpinLimit) {
                if (c < i) {
                    const bool split = is_attn && c == n - 2;
                    const uint32_t bar = split ? bar_last + 8 * part : bar_full + 8 * cst;
                    const uint32_t par = split ? 0 : cph;
                    if (i == n) mbar_wait(bar, par);
                    if ((i == n || mbar_test(bar, par)) && (!split || ++part == 8)) {
                        c++;
                        if (++cst == NST) { cst = 0; cph ^= 1; }
                        if (kResident && is_attn) red_inc(&g_sync[0], kLandedWrap);
                    }
                }
                if (i < n) {
                    const int fl = i - c;
                    if (idle > kPaceLimit) paced = false;
                    bool go;
                    if (i < kFree1) go = fl < kWin1;
                    else if (i < kFree2 || !paced) go = fl < kWin2;
                    else go = c == ntrack ||
                              (fl < NST && 256 * fl < 128 * kPaceWin2x + kPaceGain2x * ((int)lds32_volatile(sb + OFF_PACE) - 128 * c));
                    if (go && mbar_test(bar_empty + 8 * ist, iph)) {
                        if (is_attn && i >= n - 2) {
                            const int k = i - (n - 2);
                            const char* src = p.v + ((size_t)(((cta & 3) + 4) * kH + (cta >> 2)) << 20) + ((size_t)(TILES - 2 + k) << 15);
#pragma unroll 1
                            for (int j = 0; j < 8; j++) {
                                mbar_expect(bar_last + 64 * k + 8 * j, STAGE / 8);
                                bulk_load(sb + ist * STAGE + j * (STAGE / 8), src + j * (STAGE / 8), STAGE / 8, bar_last + 64 * k + 8 * j, pol);
                            }
                            if (k == 1) sts32_volatile(sb + OFF_PACE + 4, 1);
                        } else {
                            issue_tile(cta, i, sb + ist * STAGE, bar_full + 8 * ist, p, pol, &tm_wo, &tm_wg, &tm_wu, &tm_wd);
                        }
                        i++;
                        idle = 0;
                        if (++ist == NST) { ist = 0; iph ^= 1; }
                    }
                }
            }
        } else if (tid == 64 && is_attn && kResident) {
            uint32_t it = 0;
            while (!lds32_volatile(sb + OFF_PACE + 4) && ++it < kSleepLimit) {
                sts32_volatile(sb + OFF_PACE, load_relaxed(&g_sync[0]));
                __nanosleep(200);
            }
        } else if (tid == 32 && is_attn) {
            uint32_t it = 0;
            do {
                __nanosleep(4000);
            } while (load_relaxed(&g_sync[64]) < 2 * kGluCtas && ++it < kSleepLimit);
            fence_gpu();
            mbar_arrive(bar_gate);
            red_inc(&g_sync[64], kStageWrap);
        }
    } else {
        asm volatile("setmaxnreg.inc.sync.aligned.u32 232;");
        const int g = lane >> 2, t = lane & 3, mi = lane >> 3, r = lane & 7;
        Ring ring{bar_full, bar_empty, sb, 0u, 0u};

        if (ln_warp) {
            const uint32_t w[8] = {xv0.x, xv0.y, xv0.z, xv0.w, xv1.x, xv1.y, xv1.z, xv1.w};
            float f[16];
            float sum = 0.f;
#pragma unroll
            for (int i = 0; i < 8; i++) {
                f[2 * i] = bf_lo(w[i]);
                f[2 * i + 1] = bf_hi(w[i]);
                sum += f[2 * i] + f[2 * i + 1];
            }
#pragma unroll
            for (int o = 16; o; o >>= 1) sum += __shfl_xor_sync(0xffffffffu, sum, o);
            const float mean = sum * (1.0f / kD);
            float var = 0.f;
#pragma unroll
            for (int i = 0; i < 16; i++) var += (f[i] - mean) * (f[i] - mean);
#pragma unroll
            for (int o = 16; o; o >>= 1) var += __shfl_xor_sync(0xffffffffu, var, o);
            const float mb = bf16r(mean);
            const float den = bf16r(fsqrt(bf16r(bf16r(var * (1.0f / kD)) + 1e-5f)));
            uint32_t o8[8];
#pragma unroll
            for (int i = 0; i < 8; i++) o8[i] = pack_bf16(fdiv(bf16r(f[2 * i] - mb), den), fdiv(bf16r(f[2 * i + 1] - mb), den));
            const uint32_t xr = sb + OFF_XN + ln_row * XN_STRIDE + lane * 16;
            sts128(xr, o8[0], o8[1], o8[2], o8[3]);
            sts128(xr + 512, o8[4], o8[5], o8[6], o8[7]);
            if (is_attn) {
                sts128(sb + OFF_XR + ln_row * 1024 + lane * 16, w[0], w[1], w[2], w[3]);
                sts128(sb + OFF_XR + ln_row * 1024 + 512 + lane * 16, w[4], w[5], w[6], w[7]);
            }
        }
        bar_consumers();

        if (is_attn) {
            {
                float qa[4] = {0.f, 0.f, 0.f, 0.f}, qb[4] = {0.f, 0.f, 0.f, 0.f};
                const uint32_t aoff = (cw >> 2) * 16384 + ((mi >> 1) * 8 + r) * 128 + (((2 * (cw & 3) + (mi & 1)) ^ r) << 4);
                const uint32_t boff = sb + OFF_XN + (r & 1) * XN_STRIDE + mi * 16;
#pragma unroll 1
                for (int i = 0; i < 4; i++) {
                    const uint32_t base = ring.acquire() + aoff;
#pragma unroll
                    for (int s2 = 0; s2 < 4; s2++) {
                        uint32_t b[4], a0[4], a1[4];
                        ldsm4(b, boff + i * 256 + s2 * 64);
                        ldsm4t(a0, base + s2 * 4096);
                        ldsm4t(a1, base + s2 * 4096 + 2048);
                        mma16816(qa, a0, b[0], b[1]);
                        mma16816(qb, a1, b[2], b[3]);
                    }
                    ring.release(lane);
                }
                if (t == 0) {
                    const uint32_t qd = sb + OFF_QS + (16 * cw + g) * 2;
                    sts16(qd, qa[0] + qb[0]);
                    sts16(qd + 256, qa[1] + qb[1]);
                    sts16(qd + 16, qa[2] + qb[2]);
                    sts16(qd + 256 + 16, qa[3] + qb[3]);
                }
                bar_consumers();
            }

            uint32_t wo[8][4][4];
            const bool diag = t == (g >> 1);
            const uint32_t sel0 = diag ? ((g & 1) ? 0x1044u : 0x4410u) : 0x4444u;
            const uint32_t sel1 = diag ? ((g & 1) ? 0x3244u : 0x4432u) : 0x4444u;
            const uint32_t sc = sb + OFF_SC + cw * 1024;
            const uint32_t red = sb + OFF_RED;
            const uint32_t koff = (16 * cw + (mi & 1) * 8 + r) * 256 + (((mi >> 1) ^ r) << 4);
            const uint32_t voff = (16 * cw + (mi >> 1) * 8 + r) * 256 + (((mi & 1) ^ r) << 4);

#pragma unroll 1
            for (int bb = 0; bb < 2; bb++) {
                float mx = -INFINITY;
                {
                    uint32_t bq[8][2];
#pragma unroll
                    for (int j = 0; j < 8; j++) {
                        bq[j][0] = lds32(sb + OFF_QS + bb * 256 + (((2 * j) ^ g) << 4) + t * 4);
                        bq[j][1] = lds32(sb + OFF_QS + bb * 256 + (((2 * j + 1) ^ g) << 4) + t * 4);
                    }
#pragma unroll 1
                    for (int tile = 0; tile < TILES; tile++) {
                        if (bb == 0 && tile == WO_POS) {
#pragma unroll
                            for (int i = 0; i < 4; i++) {
                                const uint32_t base = ring.acquire() + cw * 4096;
#pragma unroll
                                for (int ks = 0; ks < 2; ks++)
#pragma unroll
                                    for (int mt = 0; mt < 4; mt++)
                                        ldsm4t(wo[2 * i + ks][mt],
                                               base + (16 * ks + (mi >> 1) * 8 + r) * 128 + (((2 * mt + (mi & 1)) ^ r) << 4));
                                ring.release(lane);
                            }
                        }
                        const uint32_t base = ring.acquire();
                        float c0[4] = {0.f, 0.f, 0.f, 0.f}, c1[4] = {0.f, 0.f, 0.f, 0.f};
#pragma unroll
                        for (int j = 0; j < 8; j += 2) {
                            uint32_t a0[4], a1[4];
                            ldsm4(a0, base + (koff ^ (j << 5)));
                            ldsm4(a1, base + (koff ^ ((j + 1) << 5)));
                            mma16816(c0, a0, bq[j][0], bq[j][1]);
                            mma16816(c1, a1, bq[j + 1][0], bq[j + 1][1]);
                        }
                        ring.release(lane);
                        const float d0 = (g & 1) ? c0[1] + c1[1] : c0[0] + c1[0];
                        const float d1 = (g & 1) ? c0[3] + c1[3] : c0[2] + c1[2];
                        const float scale = 0.08838834764831845f;
                        const uint32_t sp = pack_bf16(bf16r(d0) * scale, bf16r(d1) * scale);
                        if (diag) {
                            mx = fmaxf(mx, fmaxf(bf_lo(sp), bf_hi(sp)));
                            sts32(sc + (tile * 8 + g) * 4, sp);
                        }
                    }
                }
                {
#pragma unroll
                    for (int o = 16; o; o >>= 1) mx = fmaxf(mx, __shfl_xor_sync(0xffffffffu, mx, o));
                    if (lane == 0) sts32(red + cw * 4, __float_as_uint(mx));
                    bar_consumers();
                    const uint4 m0 = lds128(red), m1 = lds128(red + 16);
                    mx = fmaxf(fmaxf(fmaxf(__uint_as_float(m0.x), __uint_as_float(m0.y)), fmaxf(__uint_as_float(m0.z), __uint_as_float(m0.w))),
                               fmaxf(fmaxf(__uint_as_float(m1.x), __uint_as_float(m1.y)), fmaxf(__uint_as_float(m1.z), __uint_as_float(m1.w))));
                    const uint4 s0 = lds128(sc + lane * 16), s1 = lds128(sc + 512 + lane * 16);
                    const uint32_t w[8] = {s0.x, s0.y, s0.z, s0.w, s1.x, s1.y, s1.z, s1.w};
                    float e[16];
                    float sum = 0.f;
                    const float log2e = 1.4426950408889634f;
#pragma unroll
                    for (int i = 0; i < 8; i++) {
                        e[2 * i] = exp2f((bf_lo(w[i]) - mx) * log2e);
                        e[2 * i + 1] = exp2f((bf_hi(w[i]) - mx) * log2e);
                        sum += e[2 * i] + e[2 * i + 1];
                    }
#pragma unroll
                    for (int o = 16; o; o >>= 1) sum += __shfl_xor_sync(0xffffffffu, sum, o);
                    if (lane == 0) sts32(red + 32 + cw * 4, __float_as_uint(sum));
                    bar_consumers();
                    const uint4 t0 = lds128(red + 32), t1 = lds128(red + 48);
                    const float tot = ((__uint_as_float(t0.x) + __uint_as_float(t0.y)) + (__uint_as_float(t0.z) + __uint_as_float(t0.w))) +
                                      ((__uint_as_float(t1.x) + __uint_as_float(t1.y)) + (__uint_as_float(t1.z) + __uint_as_float(t1.w)));
                    const float inv = fdiv(1.0f, tot);
                    sts128(sc + lane * 16, pack_bf16(e[0] * inv, e[1] * inv), pack_bf16(e[2] * inv, e[3] * inv),
                           pack_bf16(e[4] * inv, e[5] * inv), pack_bf16(e[6] * inv, e[7] * inv));
                    sts128(sc + 512 + lane * 16, pack_bf16(e[8] * inv, e[9] * inv), pack_bf16(e[10] * inv, e[11] * inv),
                           pack_bf16(e[12] * inv, e[13] * inv), pack_bf16(e[14] * inv, e[15] * inv));
                    __syncwarp();
                }
                const int col = 64 * cw + 16 * t + g;
                float4* slot = g_acc + ((cta & 3) + 4 * bb) * 256 + cw * 32 + lane;
                unsigned short* outp = reinterpret_cast<unsigned short*>(p.out) + ((cta & 3) + 4 * bb) * kD + col;
                float x0 = __uint_as_float(lds16(sb + OFF_XR + bb * 1024 + col * 2) << 16);
                float x1 = __uint_as_float(lds16(sb + OFF_XR + bb * 1024 + col * 2 + 16) << 16);
                uint32_t ob_st = sb + OFF_OB + cw * OB_STRIDE + (16 * t + g) * 2;
                uint32_t ob_ld = sb + OFF_OB + r * OB_STRIDE + mi * 16;
                asm volatile("" : "+l"(slot), "+l"(outp), "+f"(x0), "+f"(x1), "+r"(ob_st), "+r"(ob_ld));
                float acc[8][4];
#pragma unroll
                for (int j = 0; j < 8; j++) acc[j][0] = acc[j][1] = acc[j][2] = acc[j][3] = 0.f;
                auto v_tile = [&](uint32_t pw, uint32_t st, uint32_t bar, uint32_t par, bool wait) {
                    uint32_t b0 = __byte_perm(pw, 0, sel0), b1 = __byte_perm(pw, 0, sel1);
                    const uint32_t base = ring.data0 + st * STAGE;
                    uint32_t va[4] = {base + voff, base + (voff ^ 32), base + (voff ^ 64), base + (voff ^ 96)};
                    asm volatile("" : "+r"(va[0]), "+r"(va[1]), "+r"(va[2]), "+r"(va[3]), "+r"(b0), "+r"(b1));
                    if (wait) mbar_wait(bar, par);
#pragma unroll
                    for (int jj = 0; jj < 8; jj++) {
                        const int j = 3 - (jj >> 1) + 4 * (jj & 1);
                        uint32_t a[4];
                        ldsm4t(a, va[j & 3] + (j >> 2) * 128);
                        mma16816(acc[j], a, b0, b1);
                    }
                };
#pragma unroll 1
                for (int tile = 0; tile < TILES - 2; tile++) {
                    if (tile == TILES - 3) mbar_wait(bar_gate, 0);
                    v_tile(lds32(sc + (tile * 8 + g) * 4), ring.st, ring.full0 + 8 * ring.st, ring.ph, true);
                    ring.release(lane);
                }
                {
                    const uint32_t pwa = lds32(sc + ((TILES - 2) * 8 + g) * 4), pwb = lds32(sc + ((TILES - 1) * 8 + g) * 4);
                    const uint32_t sta = ring.st, stb = sta + 1 == NST ? 0 : sta + 1;
                    const uint32_t bara = bb ? bar_last + 8 * cw : ring.full0 + 8 * sta;
                    const uint32_t barb = bb ? bar_last + 64 + 8 * cw : ring.full0 + 8 * stb;
                    const uint32_t para = bb ? 0 : ring.ph, parb = bb ? 0 : ring.ph ^ (stb == 0);
                    bool a_first;
                    uint32_t it = 0;
                    while (true) {
                        const bool ra = mbar_test(bara, para), rb = mbar_test(barb, parb);
                        a_first = __all_sync(0xffffffffu, ra);
                        if (a_first || __all_sync(0xffffffffu, rb) || ++it > kSpinLimit) break;
                    }
                    v_tile(a_first ? pwa : pwb, a_first ? sta : stb, 0, 0, false);
                    v_tile(a_first ? pwb : pwa, a_first ? stb : sta, a_first ? barb : bara, a_first ? parb : para, true);
                }
                {
                    float ev[8], od[8];
#pragma unroll
                    for (int j = 0; j < 8; j++) {
                        ev[j] = acc[j][0] + acc[j][3];
                        od[j] = acc[j][1] + acc[j][2];
                    }
#pragma unroll
                    for (int j = 0; j < 8; j += 2) {
                        ev[j] += __shfl_xor_sync(0xffffffffu, ev[j + 1], 1);
                        od[j] += __shfl_xor_sync(0xffffffffu, od[j + 1], 1);
                    }
#pragma unroll
                    for (int j = 0; j < 8; j += 4) {
                        ev[j] += __shfl_xor_sync(0xffffffffu, ev[j + 2], 2);
                        od[j] += __shfl_xor_sync(0xffffffffu, od[j + 2], 2);
                    }
                    sts16(ob_st, ev[0]);
                    sts16(ob_st + 16, od[0]);
                    sts16(ob_st + 128, ev[4]);
                    sts16(ob_st + 144, od[4]);
                }
                bar_consumers();
                {
                    float pc[4][4];
#pragma unroll
                    for (int mt = 0; mt < 4; mt++) pc[mt][0] = pc[mt][1] = pc[mt][2] = pc[mt][3] = 0.f;
#pragma unroll
                    for (int s2 = 0; s2 < 4; s2++) {
                        uint32_t b[4];
                        ldsm4(b, ob_ld + s2 * 64);
#pragma unroll
                        for (int mt = 0; mt < 4; mt++) mma16816(pc[mt], wo[2 * s2][mt], b[0], b[1]);
#pragma unroll
                        for (int mt = 0; mt < 4; mt++) mma16816(pc[mt], wo[2 * s2 + 1][mt], b[2], b[3]);
                    }
                    float lo[4], hi[4];
#pragma unroll
                    for (int mt = 0; mt < 4; mt++) {
                        lo[mt] = pc[mt][0] + pc[mt][1];
                        hi[mt] = pc[mt][2] + pc[mt][3];
                    }
                    const bool t1 = t & 1, t2 = t & 2;
                    const float yl0 = (t1 ? lo[1] : lo[0]) + __shfl_xor_sync(0xffffffffu, t1 ? lo[0] : lo[1], 1);
                    const float yl1 = (t1 ? lo[3] : lo[2]) + __shfl_xor_sync(0xffffffffu, t1 ? lo[2] : lo[3], 1);
                    const float yh0 = (t1 ? hi[1] : hi[0]) + __shfl_xor_sync(0xffffffffu, t1 ? hi[0] : hi[1], 1);
                    const float yh1 = (t1 ? hi[3] : hi[2]) + __shfl_xor_sync(0xffffffffu, t1 ? hi[2] : hi[3], 1);
                    const float zl = (t2 ? yl1 : yl0) + __shfl_xor_sync(0xffffffffu, t2 ? yl0 : yl1, 2);
                    const float zh = (t2 ? yh1 : yh0) + __shfl_xor_sync(0xffffffffu, t2 ? yh0 : yh1, 2);
                    out_arrive(slot, zl, zh, x0, x1, outp);
                    ring.release(lane);
                    ring.release(lane);
                }
            }
        } else {
            float ga[4][4], ua[4][4];
#pragma unroll
            for (int mt = 0; mt < 4; mt++)
#pragma unroll
                for (int i = 0; i < 4; i++) ga[mt][i] = ua[mt][i] = 0.f;
            const uint32_t xb = sb + OFF_XN + r * XN_STRIDE + mi * 16;
#pragma unroll 1
            for (int i = 0; i < 16; i++) {
                const uint32_t base = ring.acquire();
                if (cw < 7) gemm_block32(ga, base + cw * 4096, xb + i * 64, lane);
                ring.release(lane);
            }
#pragma unroll 1
            for (int i = 0; i < 16; i++) {
                const uint32_t base = ring.acquire();
                if (cw < 7) gemm_block32(ua, base + cw * 4096, xb + i * 64, lane);
                ring.release(lane);
            }
            const uint32_t hs = sb + OFF_SC;
            if (cw < 7) {
#pragma unroll
                for (int mt = 0; mt < 4; mt++)
#pragma unroll
                    for (int i = 0; i < 4; i++)
                        sts16(hs + (2 * t + (i & 1)) * HS_STRIDE + (64 * cw + 16 * mt + g + (i >> 1) * 8) * 2,
                              bf16r(ga[mt][i]) * bf16r(ua[mt][i]));
            }
            bar_consumers();
#pragma unroll
            for (int mt = 0; mt < 4; mt++)
#pragma unroll
                for (int i = 0; i < 4; i++) ga[mt][i] = 0.f;
#pragma unroll 1
            for (int i = 0; i < 14; i++) {
                const uint32_t base = ring.acquire();
                gemm_block32(ga, base + cw * 4096, hs + r * HS_STRIDE + mi * 16 + i * 64, lane);
                ring.release(lane);
            }
            const int j = cta - kAttnCtas;
#pragma unroll
            for (int e = 0; e < 2; e++) {
                float4* dst = reinterpret_cast<float4*>(g_glu + (j * kB + 2 * t + e) * 256 + cw * 32 + g * 4);
                dst[0] = make_float4(ga[0][e], ga[0][2 + e], ga[1][e], ga[1][2 + e]);
                dst[1] = make_float4(ga[2][e], ga[2][2 + e], ga[3][e], ga[3][2 + e]);
            }
            bar_consumers();
            if (tid == 128) {
                fence_gpu();
                red_inc(&g_sync[64], kStageWrap);
                uint32_t it = 0;
                while (load_relaxed(&g_sync[64]) < kGluCtas && ++it < kSleepLimit) __nanosleep(200);
                fence_gpu();
            }
            bar_consumers();
            const int si = j * 512 + (tid - 128) * 2;
            float4 d = make_float4(0.f, 0.f, 0.f, 0.f);
#pragma unroll
            for (int k = 0; k < kGluCtas; k++) {
                const float4 v = __ldcg(reinterpret_cast<const float4*>(g_glu + k * kB * 256 + si));
                d.x += v.x; d.y += v.y; d.z += v.z; d.w += v.w;
            }
            const float dd[4] = {bf16r(d.x), bf16r(d.y), bf16r(d.z), bf16r(d.w)};
            float gb[4];
#pragma unroll
            for (int k = 0; k < 4; k++) gb[k] = (float)(pack_bf16(fdiv(dd[k], 1.0f + expf(-dd[k])), 0.f) & 0xffffu);
            g_acc[si] = make_float4(0.f, 0.f, gb[0], gb[1]);
            g_acc[si + 1] = make_float4(0.f, 0.f, gb[2], gb[3]);
            bar_consumers();
            if (tid == 128) {
                fence_gpu();
                red_inc(&g_sync[64], kStageWrap);
            }
        }
    }
}

typedef CUresult (*EncodeFn)(CUtensorMap*, CUtensorMapDataType, cuuint32_t, void*, const cuuint64_t*, const cuuint64_t*,
                             const cuuint32_t*, const cuuint32_t*, CUtensorMapInterleave, CUtensorMapSwizzle,
                             CUtensorMapL2promotion, CUtensorMapFloatOOBfill);

void encode_weight(EncodeFn fn, CUtensorMap* m, void* ptr, int rows, int cols, int box_rows, int box_grps) {
    cuuint64_t dims[3] = {64, (cuuint64_t)rows, (cuuint64_t)(cols / 64)};
    cuuint64_t strides[2] = {(cuuint64_t)cols * 2, 128};
    cuuint32_t box[3] = {64, (cuuint32_t)box_rows, (cuuint32_t)box_grps};
    cuuint32_t es[3] = {1, 1, 1};
    fn(m, CU_TENSOR_MAP_DATA_TYPE_BFLOAT16, 3, ptr, dims, strides, box, es, CU_TENSOR_MAP_INTERLEAVE_NONE,
       CU_TENSOR_MAP_SWIZZLE_128B, CU_TENSOR_MAP_L2_PROMOTION_NONE, CU_TENSOR_MAP_FLOAT_OOB_FILL_NONE);
}

}

extern "C" void kernel_launch(void* const* d_in, const int* in_sizes, int n_in, void* d_out, int out_size) {
    static EncodeFn encode = nullptr;
    static bool resident = false;
    if (!encode) {
        void* fn = nullptr;
        cudaDriverEntryPointQueryResult qr;
        cudaGetDriverEntryPoint("cuTensorMapEncodeTiled", &fn, cudaEnableDefault, &qr);
        encode = (EncodeFn)fn;
        cudaFuncSetAttribute(fused_decode_kernel<true>, cudaFuncAttributeMaxDynamicSharedMemorySize, SMEM_BYTES);
        cudaFuncSetAttribute(fused_decode_kernel<false>, cudaFuncAttributeMaxDynamicSharedMemorySize, SMEM_BYTES);
        int dev = 0, sms = 0;
        cudaGetDevice(&dev);
        cudaDeviceGetAttribute(&sms, cudaDevAttrMultiProcessorCount, dev);
        resident = sms >= kGrid;
    }
    Params p;
    p.x = (const __nv_bfloat16*)d_in[0];
    p.k = (const char*)d_in[1];
    p.v = (const char*)d_in[2];
    p.out = (__nv_bfloat16*)d_out;
    CUtensorMap tm_wq, tm_wo, tm_wg, tm_wu, tm_wd;
    encode_weight(encode, &tm_wq, d_in[3], kD, kH * kDh, 128, 2);
    encode_weight(encode, &tm_wo, d_in[4], kH * kDh, kD, 32, 8);
    encode_weight(encode, &tm_wg, d_in[6], kD, kF, 32, 7);
    encode_weight(encode, &tm_wu, d_in[7], kD, kF, 32, 7);
    encode_weight(encode, &tm_wd, d_in[8], kF, kD, 32, 8);
    if (resident)
        fused_decode_kernel<true><<<kGrid, kThreads, SMEM_BYTES>>>(p, tm_wq, tm_wo, tm_wg, tm_wu, tm_wd);
    else
        fused_decode_kernel<false><<<kGrid, kThreads, SMEM_BYTES>>>(p, tm_wq, tm_wo, tm_wg, tm_wu, tm_wd);
}
```

```cpp
#include <cuda_runtime.h>
#include <cuda_bf16.h>
#include <cuda.h>
#include <stdint.h>

namespace {

constexpr int kB = 8, kD = 512, kH = 32, kSk = 4096, kDh = 128, kF = 1792;
constexpr int kAttnCtas = 128, kGluCtas = 4, kGrid = kAttnCtas + kGluCtas;
constexpr int kThreads = 384;

constexpr int NST = 6;
constexpr int STAGE = 32768;
constexpr int TILES = kSk / 128;
constexpr int WO_POS = 2;
constexpr int kAttnTiles = 8 + 4 * TILES;
constexpr int kGluTiles = 46;

constexpr int kFree1 = 12, kWin1 = 6, kFree2 = 16, kWin2 = 3;
constexpr int kPaceWin2x = 6, kPaceGain2x = 3;

constexpr int XN_STRIDE = 1040;
constexpr int HS_STRIDE = 912;
constexpr int OB_STRIDE = 272;

constexpr int OFF_SC = NST * STAGE;
constexpr int OFF_XN = OFF_SC + 8192;
constexpr int OFF_XR = OFF_XN + 8 * XN_STRIDE;
constexpr int OFF_QS = OFF_XR + 2 * 1024;
constexpr int OFF_OB = OFF_QS + 512;
constexpr int OFF_RED = OFF_OB + 8 * OB_STRIDE;
constexpr int OFF_BAR = OFF_RED + 64;
constexpr int OFF_PACE = OFF_BAR + 8 * (2 * NST + 1 + 16);
constexpr int SMEM_BYTES = OFF_PACE + 8;

constexpr uint32_t kTryLimit = 1u << 13;
constexpr uint32_t kSpinLimit = 1u << 21;
constexpr uint32_t kSleepLimit = 1u << 17;
constexpr uint32_t kPaceLimit = 1u << 15;

__device__ __align__(1024) float4 g_acc[kB * 256];
__device__ __align__(1024) float2 g_glu[kGluCtas * kB * 256];
__device__ __align__(1024) uint32_t g_sync[128];
constexpr uint32_t kLandedWrap = kAttnCtas * (kAttnTiles - 1) - 1;
constexpr uint32_t kStageWrap = 2 * kGluCtas + kAttnCtas - 1;

__device__ __forceinline__ uint32_t smem_u32(const void* p) { return (uint32_t)__cvta_generic_to_shared(p); }

__device__ __forceinline__ void mbar_init(uint32_t bar, uint32_t cnt) {
    asm volatile("mbarrier.init.shared.b64 [%0], %1;" ::"r"(bar), "r"(cnt) : "memory");
}
__device__ __forceinline__ void mbar_expect(uint32_t bar, uint32_t bytes) {
    asm volatile("mbarrier.arrive.expect_tx.shared.b64 _, [%0], %1;" ::"r"(bar), "r"(bytes) : "memory");
}
__device__ __forceinline__ void mbar_arrive(uint32_t bar) {
    asm volatile("mbarrier.arrive.shared.b64 _, [%0];" ::"r"(bar) : "memory");
}
__device__ __forceinline__ void mbar_wait(uint32_t bar, uint32_t parity) {
    uint32_t ok, it = 0;
    do {
        asm volatile("{.reg .pred p; mbarrier.try_wait.parity.shared.b64 p, [%1], %2; selp.u32 %0, 1, 0, p;}"
                     : "=r"(ok) : "r"(bar), "r"(parity) : "memory");
        if (++it > kTryLimit) break;
    } while (!ok);
}
__device__ __forceinline__ bool mbar_test(uint32_t bar, uint32_t parity) {
    uint32_t ok;
    asm volatile("{.reg .pred p; mbarrier.test_wait.parity.shared.b64 p, [%1], %2; selp.u32 %0, 1, 0, p;}"
                 : "=r"(ok) : "r"(bar), "r"(parity) : "memory");
    return ok;
}
__device__ __forceinline__ void bulk_load(uint32_t dst, const void* src, uint32_t bytes, uint32_t bar, uint64_t pol) {
    asm volatile("cp.async.bulk.shared::cluster.global.mbarrier::complete_tx::bytes.L2::cache_hint [%0], [%1], %2, [%3], %4;"
                 ::"r"(dst), "l"(src), "r"(bytes), "r"(bar), "l"(pol) : "memory");
}
__device__ __forceinline__ void tma_load3(uint32_t dst, const CUtensorMap* m, int row, int grp, uint32_t bar) {
    asm volatile("cp.async.bulk.tensor.3d.shared::cluster.global.mbarrier::complete_tx::bytes [%0], [%1, {%3, %4, %5}], [%2];"
                 ::"r"(dst), "l"(m), "r"(bar), "r"(0), "r"(row), "r"(grp) : "memory");
}
__device__ __forceinline__ void ldsm4(uint32_t (&r)[4], uint32_t addr) {
    asm volatile("ldmatrix.sync.aligned.m8n8.x4.shared.b16 {%0,%1,%2,%3}, [%4];"
                 : "=r"(r[0]), "=r"(r[1]), "=r"(r[2]), "=r"(r[3]) : "r"(addr) : "memory");
}
__device__ __forceinline__ void ldsm4t(uint32_t (&r)[4], uint32_t addr) {
    asm volatile("ldmatrix.sync.aligned.m8n8.x4.trans.shared.b16 {%0,%1,%2,%3}, [%4];"
                 : "=r"(r[0]), "=r"(r[1]), "=r"(r[2]), "=r"(r[3]) : "r"(addr) : "memory");
}
__device__ __forceinline__ void mma16816(float (&c)[4], const uint32_t (&a)[4], uint32_t b0, uint32_t b1) {
    asm volatile("mma.sync.aligned.m16n8k16.row.col.f32.bf16.bf16.f32 {%0,%1,%2,%3}, {%4,%5,%6,%7}, {%8,%9}, {%0,%1,%2,%3};"
                 : "+f"(c[0]), "+f"(c[1]), "+f"(c[2]), "+f"(c[3])
                 : "r"(a[0]), "r"(a[1]), "r"(a[2]), "r"(a[3]), "r"(b0), "r"(b1));
}
__device__ __forceinline__ void bar_consumers() { asm volatile("bar.sync 1, 256;" ::: "memory"); }

__device__ __forceinline__ uint32_t pack_bf16(float lo, float hi) {
    uint32_t r;
    asm("cvt.rn.bf16x2.f32 %0, %1, %2;" : "=r"(r) : "f"(hi), "f"(lo));
    return r;
}
__device__ __forceinline__ float bf16r(float x) { return __uint_as_float(pack_bf16(0.f, x)); }
__device__ __forceinline__ float fdiv(float a, float b) {
    float r;
    asm("div.full.f32 %0, %1, %2;" : "=f"(r) : "f"(a), "f"(b));
    return r;
}
__device__ __forceinline__ float fsqrt(float a) {
    float r;
    asm("sqrt.approx.f32 %0, %1;" : "=f"(r) : "f"(a));
    return r;
}
__device__ __forceinline__ float bf_lo(uint32_t v) { return __uint_as_float(v << 16); }
__device__ __forceinline__ float bf_hi(uint32_t v) { return __uint_as_float(v & 0xffff0000u); }

__device__ __forceinline__ void sts16(uint32_t addr, float v) {
    asm volatile("st.shared.b16 [%0], %1;" ::"r"(addr), "h"((unsigned short)pack_bf16(v, 0.f)) : "memory");
}
__device__ __forceinline__ void sts32(uint32_t addr, uint32_t v) {
    asm volatile("st.shared.b32 [%0], %1;" ::"r"(addr), "r"(v) : "memory");
}
__device__ __forceinline__ void sts128(uint32_t addr, uint32_t a, uint32_t b, uint32_t c, uint32_t d) {
    asm volatile("st.shared.v4.b32 [%0], {%1,%2,%3,%4};" ::"r"(addr), "r"(a), "r"(b), "r"(c), "r"(d) : "memory");
}
__device__ __forceinline__ uint32_t lds32(uint32_t addr) {
    uint32_t v;
    asm volatile("ld.shared.b32 %0, [%1];" : "=r"(v) : "r"(addr) : "memory");
    return v;
}
__device__ __forceinline__ uint32_t lds32_volatile(uint32_t addr) {
    uint32_t v;
    asm volatile("ld.volatile.shared.b32 %0, [%1];" : "=r"(v) : "r"(addr) : "memory");
    return v;
}
__device__ __forceinline__ void sts32_volatile(uint32_t addr, uint32_t v) {
    asm volatile("st.volatile.shared.b32 [%0], %1;" ::"r"(addr), "r"(v) : "memory");
}
__device__ __forceinline__ uint4 lds128(uint32_t addr) {
    uint4 v;
    asm volatile("ld.shared.v4.b32 {%0,%1,%2,%3}, [%4];" : "=r"(v.x), "=r"(v.y), "=r"(v.z), "=r"(v.w) : "r"(addr) : "memory");
    return v;
}
__device__ __forceinline__ uint32_t lds16(uint32_t addr) {
    unsigned short v;
    asm volatile("ld.shared.b16 %0, [%1];" : "=h"(v) : "r"(addr) : "memory");
    return v;
}
__device__ __forceinline__ float4 slot_arrive(float4* slot, float s0, float s1) {
    float4 o;
    asm volatile("atom.relaxed.gpu.global.add.v4.f32 {%0,%1,%2,%3}, [%4], {%5,%6,%7,%8};"
                 : "=f"(o.x), "=f"(o.y), "=f"(o.z), "=f"(o.w)
                 : "l"(slot), "f"(s0), "f"(s1), "f"(65536.f), "f"(0.f) : "memory");
    return o;
}
__device__ __forceinline__ void slot_finish(const float4 o, float s0, float s1, float x0, float x1, unsigned short* outp) {
    const float g0 = __uint_as_float(__float_as_uint(o.z + 8388608.f) << 16);
    const float g1 = __uint_as_float(__float_as_uint(o.w + 8388608.f) << 16);
    const uint32_t r0 = pack_bf16(x0 + bf16r(bf16r(o.x + s0) * g0), 0.f);
    const uint32_t r1 = pack_bf16(x1 + bf16r(bf16r(o.y + s1) * g1), 0.f);
    asm volatile("{.reg .pred p; setp.ge.f32 p, %3, %4;\n"
                 "@p st.global.b16 [%0], %1;\n"
                 "@p st.global.b16 [%0+16], %2;}"
                 ::"l"(outp), "h"((unsigned short)r0), "h"((unsigned short)r1), "f"(o.z), "f"(65536.f * (kH - 1)) : "memory");
}
__device__ __forceinline__ void fence_gpu() { asm volatile("fence.acq_rel.gpu;" ::: "memory"); }
__device__ __forceinline__ uint32_t load_relaxed(const uint32_t* p) {
    uint32_t v;
    asm volatile("ld.relaxed.gpu.global.u32 %0, [%1];" : "=r"(v) : "l"(p) : "memory");
    return v;
}
__device__ __forceinline__ void red_inc(uint32_t* p, uint32_t limit) {
    asm volatile("red.relaxed.gpu.global.inc.u32 [%0], %1;" ::"l"(p), "r"(limit) : "memory");
}

struct Ring {
    uint32_t full0, empty0, data0;
    uint32_t st, ph;
    __device__ __forceinline__ uint32_t acquire() {
        mbar_wait(full0 + 8 * st, ph);
        return data0 + st * STAGE;
    }
    __device__ __forceinline__ void release(int lane) {
        __syncwarp();
        if (lane == 0) mbar_arrive(empty0 + 8 * st);
        if (++st == NST) { st = 0; ph ^= 1; }
    }
};

struct Params {
    const __nv_bfloat16* x;
    const char* k;
    const char* v;
    __nv_bfloat16* out;
};

__device__ __forceinline__ void issue_tile(int cta, int i, uint32_t dst, uint32_t bar, const Params& p, uint64_t pol,
                                           const CUtensorMap* tm_wo, const CUtensorMap* tm_wg, const CUtensorMap* tm_wu,
                                           const CUtensorMap* tm_wd) {
    static_assert(4 + WO_POS == NST, "the prologue issues the tiles ahead of wo");
    if (cta < kAttnCtas) {
        const int h = cta >> 2;
        mbar_expect(bar, STAGE);
        if (i < NST + 4) {
            tma_load3(dst, tm_wo, 128 * h + 32 * (i - NST), 0, bar);
        } else {
            const int c = i - 8;
            const int bh = ((cta & 3) + 4 * (c >> 6)) * kH + h;
            const char* base = (c & 32) ? p.v : p.k;
            bulk_load(dst, base + ((size_t)bh << 20) + ((size_t)(c & 31) << 15), STAGE, bar, pol);
        }
    } else {
        const int j = cta - kAttnCtas;
        if (i < 32) {
            mbar_expect(bar, 7 * 4096);
            tma_load3(dst, i < 16 ? tm_wg : tm_wu, 32 * (i & 15), 7 * j, bar);
        } else {
            mbar_expect(bar, STAGE);
            tma_load3(dst, tm_wd, 448 * j + 32 * (i - 32), 0, bar);
        }
    }
}

__device__ __forceinline__ void gemm_block32(float (&acc)[4][4], uint32_t wbase, uint32_t baddr, int lane) {
    const int mi = lane >> 3, r = lane & 7;
    uint32_t b[4];
    ldsm4(b, baddr);
#pragma unroll
    for (int ks = 0; ks < 2; ks++) {
#pragma unroll
        for (int mt = 0; mt < 4; mt++) {
            uint32_t a[4];
            ldsm4t(a, wbase + (16 * ks + (mi >> 1) * 8 + r) * 128 + (((2 * mt + (mi & 1)) ^ r) << 4));
            mma16816(acc[mt], a, b[2 * ks], b[2 * ks + 1]);
        }
    }
}

template <bool kResident>
__global__ void __launch_bounds__(kThreads, 1)
fused_decode_kernel(const Params p,
                    const __grid_constant__ CUtensorMap tm_wq, const __grid_constant__ CUtensorMap tm_wo,
                    const __grid_constant__ CUtensorMap tm_wg, const __grid_constant__ CUtensorMap tm_wu,
                    const __grid_constant__ CUtensorMap tm_wd) {
    extern __shared__ __align__(1024) char smem[];
    const uint32_t sb = smem_u32(smem);
    const uint32_t bar_full = sb + OFF_BAR, bar_empty = bar_full + 8 * NST;
    const uint32_t bar_gate = bar_empty + 8 * NST, bar_last = bar_gate + 8;
    const int tid = threadIdx.x, warp = tid >> 5, lane = tid & 31;
    const int blk33 = blockIdx.x / 33;
    const bool is_attn = kResident ? blockIdx.x - blk33 * 33 != 32 : blockIdx.x >= kGluCtas;
    const int cta = kResident ? (is_attn ? blockIdx.x - blk33 : kAttnCtas + blk33)
                              : (is_attn ? blockIdx.x - kGluCtas : kAttnCtas + blockIdx.x);

    uint64_t pol;
    asm volatile("createpolicy.fractional.L2::evict_first.b64 %0, 1.0;" : "=l"(pol));
    uint4 xv0 = make_uint4(0, 0, 0, 0), xv1 = xv0;
    const int cw = warp - 4;
    const bool ln_warp = is_attn ? cw >= 6 : cw >= 0;
    const int ln_row = is_attn ? cw - 6 : cw;
    const char* k0 = p.k + ((size_t)((cta & 3) * kH + (cta >> 2)) << 20);
    if (tid == 0) {
        mbar_init(bar_full + 8 * 4, 1);
        if (is_attn) {
            asm volatile("fence.mbarrier_init.release.cluster;" ::: "memory");
            mbar_expect(bar_full + 8 * 4, STAGE);
            bulk_load(sb + 4 * STAGE, k0, STAGE, bar_full + 8 * 4, pol);
        }
#pragma unroll
        for (int i = 0; i < NST; i++)
            if (i != 4) mbar_init(bar_full + 8 * i, 1);
        asm volatile("fence.mbarrier_init.release.cluster;" ::: "memory");
        const CUtensorMap* tm0 = is_attn ? &tm_wq : &tm_wg;
        const int rstep = is_attn ? 128 : 32, grp = is_attn ? 2 * (cta >> 2) : 7 * (cta - kAttnCtas);
        const uint32_t bytes = is_attn ? STAGE : 7 * 4096;
#pragma unroll
        for (int i = 0; i < 4; i++) {
            mbar_expect(bar_full + 8 * i, bytes);
            tma_load3(sb + i * STAGE, tm0, rstep * i, grp, bar_full + 8 * i);
        }
        if (is_attn) {
            mbar_expect(bar_full + 8 * 5, STAGE);
            bulk_load(sb + 5 * STAGE, k0 + STAGE, STAGE, bar_full + 8 * 5, pol);
        } else {
#pragma unroll
            for (int i = 4; i < NST; i++) {
                mbar_expect(bar_full + 8 * i, bytes);
                tma_load3(sb + i * STAGE, tm0, rstep * i, grp, bar_full + 8 * i);
            }
        }
    }
    if (ln_warp) {
        const uint4* xr = reinterpret_cast<const uint4*>(p.x + (is_attn ? (cta & 3) + 4 * ln_row : ln_row) * kD);
        xv0 = __ldg(xr + lane);
        xv1 = __ldg(xr + 32 + lane);
    }
    if (tid == 6 * 32) {
#pragma unroll
        for (int i = 0; i < NST; i++) mbar_init(bar_empty + 8 * i, 8);
        mbar_init(bar_gate, 1);
#pragma unroll
        for (int i = 0; i < 16; i++) mbar_init(bar_last + 8 * i, 1);
        sts32(sb + OFF_PACE, 0);
        sts32(sb + OFF_PACE + 4, 0);
        asm volatile("fence.mbarrier_init.release.cluster;" ::: "memory");
    }
    __syncthreads();

    if (warp < 4) {
        asm volatile("setmaxnreg.dec.sync.aligned.u32 40;");
        if (tid == 0) {
            const int n = is_attn ? kAttnTiles : kGluTiles;
            const int ntrack = is_attn ? n - 1 : 0;
            int i = NST, c = 0, part = 0;
            uint32_t ist = 0, iph = 0, cst = 0, cph = 0, idle = 0;
            bool paced = kResident && is_attn;
            while ((i < n || c < ntrack) && ++idle < kSpinLimit) {
                if (c < i) {
                    const bool split = is_attn && c == n - 2;
                    const uint32_t bar = split ? bar_last + 8 * part : bar_full + 8 * cst;
                    const uint32_t par = split ? 0 : cph;
                    if (i == n) mbar_wait(bar, par);
                    if ((i == n || mbar_test(bar, par)) && (!split || ++part == 8)) {
                        c++;
                        if (++cst == NST) { cst = 0; cph ^= 1; }
                        if (kResident && is_attn) red_inc(&g_sync[0], kLandedWrap);
                    }
                }
                if (i < n) {
                    const int fl = i - c;
                    if (idle > kPaceLimit) paced = false;
                    bool go;
                    if (i < kFree1) go = fl < kWin1;
                    else if (i < kFree2 || !paced) go = fl < kWin2;
                    else go = c == ntrack ||
                              (fl < NST && 256 * fl < 128 * kPaceWin2x + kPaceGain2x * ((int)lds32_volatile(sb + OFF_PACE) - 128 * c));
                    if (go && mbar_test(bar_empty + 8 * ist, iph)) {
                        if (is_attn && i >= n - 2) {
                            const int k = i - (n - 2);
                            const char* src = p.v + ((size_t)(((cta & 3) + 4) * kH + (cta >> 2)) << 20) + ((size_t)(TILES - 2 + k) << 15);
#pragma unroll 1
                            for (int j = 0; j < 8; j++) {
                                mbar_expect(bar_last + 64 * k + 8 * j, STAGE / 8);
                                bulk_load(sb + ist * STAGE + j * (STAGE / 8), src + j * (STAGE / 8), STAGE / 8, bar_last + 64 * k + 8 * j, pol);
                            }
                            if (k == 1) sts32_volatile(sb + OFF_PACE + 4, 1);
                        } else {
                            issue_tile(cta, i, sb + ist * STAGE, bar_full + 8 * ist, p, pol, &tm_wo, &tm_wg, &tm_wu, &tm_wd);
                        }
                        i++;
                        idle = 0;
                        if (++ist == NST) { ist = 0; iph ^= 1; }
                    }
                }
            }
        } else if (tid == 64 && is_attn && kResident) {
            uint32_t it = 0;
            while (!lds32_volatile(sb + OFF_PACE + 4) && ++it < kSleepLimit) {
                sts32_volatile(sb + OFF_PACE, load_relaxed(&g_sync[0]));
                __nanosleep(200);
            }
        } else if (tid == 32 && is_attn) {
            uint32_t it = 0;
            do {
                __nanosleep(4000);
            } while (load_relaxed(&g_sync[64]) < 2 * kGluCtas && ++it < kSleepLimit);
            fence_gpu();
            mbar_arrive(bar_gate);
            red_inc(&g_sync[64], kStageWrap);
        }
    } else {
        asm volatile("setmaxnreg.inc.sync.aligned.u32 232;");
        const int g = lane >> 2, t = lane & 3, mi = lane >> 3, r = lane & 7;
        Ring ring{bar_full, bar_empty, sb, 0u, 0u};

        if (ln_warp) {
            const uint32_t w[8] = {xv0.x, xv0.y, xv0.z, xv0.w, xv1.x, xv1.y, xv1.z, xv1.w};
            float f[16];
            float sum = 0.f;
#pragma unroll
            for (int i = 0; i < 8; i++) {
                f[2 * i] = bf_lo(w[i]);
                f[2 * i + 1] = bf_hi(w[i]);
                sum += f[2 * i] + f[2 * i + 1];
            }
#pragma unroll
            for (int o = 16; o; o >>= 1) sum += __shfl_xor_sync(0xffffffffu, sum, o);
            const float mean = sum * (1.0f / kD);
            float var = 0.f;
#pragma unroll
            for (int i = 0; i < 16; i++) var += (f[i] - mean) * (f[i] - mean);
#pragma unroll
            for (int o = 16; o; o >>= 1) var += __shfl_xor_sync(0xffffffffu, var, o);
            const float mb = bf16r(mean);
            const float den = bf16r(fsqrt(bf16r(bf16r(var * (1.0f / kD)) + 1e-5f)));
            uint32_t o8[8];
#pragma unroll
            for (int i = 0; i < 8; i++) o8[i] = pack_bf16(fdiv(bf16r(f[2 * i] - mb), den), fdiv(bf16r(f[2 * i + 1] - mb), den));
            const uint32_t xr = sb + OFF_XN + ln_row * XN_STRIDE + lane * 16;
            sts128(xr, o8[0], o8[1], o8[2], o8[3]);
            sts128(xr + 512, o8[4], o8[5], o8[6], o8[7]);
            if (is_attn) {
                sts128(sb + OFF_XR + ln_row * 1024 + lane * 16, w[0], w[1], w[2], w[3]);
                sts128(sb + OFF_XR + ln_row * 1024 + 512 + lane * 16, w[4], w[5], w[6], w[7]);
            }
        }
        bar_consumers();

        if (is_attn) {
            {
                float qa[4] = {0.f, 0.f, 0.f, 0.f}, qb[4] = {0.f, 0.f, 0.f, 0.f};
                const uint32_t aoff = (cw >> 2) * 16384 + ((mi >> 1) * 8 + r) * 128 + (((2 * (cw & 3) + (mi & 1)) ^ r) << 4);
                const uint32_t boff = sb + OFF_XN + (r & 1) * XN_STRIDE + mi * 16;
#pragma unroll 1
                for (int i = 0; i < 4; i++) {
                    const uint32_t base = ring.acquire() + aoff;
#pragma unroll
                    for (int s2 = 0; s2 < 4; s2++) {
                        uint32_t b[4], a0[4], a1[4];
                        ldsm4(b, boff + i * 256 + s2 * 64);
                        ldsm4t(a0, base + s2 * 4096);
                        ldsm4t(a1, base + s2 * 4096 + 2048);
                        mma16816(qa, a0, b[0], b[1]);
                        mma16816(qb, a1, b[2], b[3]);
                    }
                    ring.release(lane);
                }
                if (t == 0) {
                    const uint32_t qd = sb + OFF_QS + (16 * cw + g) * 2;
                    sts16(qd, qa[0] + qb[0]);
                    sts16(qd + 256, qa[1] + qb[1]);
                    sts16(qd + 16, qa[2] + qb[2]);
                    sts16(qd + 256 + 16, qa[3] + qb[3]);
                }
                bar_consumers();
            }

            uint32_t wo[8][4][4];
            const bool diag = t == (g >> 1);
            const uint32_t sel0 = diag ? ((g & 1) ? 0x1044u : 0x4410u) : 0x4444u;
            const uint32_t sel1 = diag ? ((g & 1) ? 0x3244u : 0x4432u) : 0x4444u;
            const uint32_t sc = sb + OFF_SC + cw * 1024;
            const uint32_t red = sb + OFF_RED;
            const uint32_t koff = (16 * cw + (mi & 1) * 8 + r) * 256 + (((mi >> 1) ^ r) << 4);
            const uint32_t voff = (16 * cw + (mi >> 1) * 8 + r) * 256 + (((mi & 1) ^ r) << 4);

#pragma unroll 1
            for (int bb = 0; bb < 2; bb++) {
                float mx = -INFINITY;
                {
                    uint32_t bq[8][2];
#pragma unroll
                    for (int j = 0; j < 8; j++) {
                        bq[j][0] = lds32(sb + OFF_QS + bb * 256 + (((2 * j) ^ g) << 4) + t * 4);
                        bq[j][1] = lds32(sb + OFF_QS + bb * 256 + (((2 * j + 1) ^ g) << 4) + t * 4);
                    }
#pragma unroll 1
                    for (int tile = 0; tile < TILES; tile++) {
                        if (bb == 0 && tile == WO_POS) {
#pragma unroll
                            for (int i = 0; i < 4; i++) {
                                const uint32_t base = ring.acquire() + cw * 4096;
#pragma unroll
                                for (int ks = 0; ks < 2; ks++)
#pragma unroll
                                    for (int mt = 0; mt < 4; mt++)
                                        ldsm4t(wo[2 * i + ks][mt],
                                               base + (16 * ks + (mi >> 1) * 8 + r) * 128 + (((2 * mt + (mi & 1)) ^ r) << 4));
                                ring.release(lane);
                            }
                        }
                        const uint32_t base = ring.acquire();
                        float c0[4] = {0.f, 0.f, 0.f, 0.f}, c1[4] = {0.f, 0.f, 0.f, 0.f};
#pragma unroll
                        for (int j = 0; j < 8; j += 2) {
                            uint32_t a0[4], a1[4];
                            ldsm4(a0, base + (koff ^ (j << 5)));
                            ldsm4(a1, base + (koff ^ ((j + 1) << 5)));
                            mma16816(c0, a0, bq[j][0], bq[j][1]);
                            mma16816(c1, a1, bq[j + 1][0], bq[j + 1][1]);
                        }
                        ring.release(lane);
                        const float d0 = (g & 1) ? c0[1] + c1[1] : c0[0] + c1[0];
                        const float d1 = (g & 1) ? c0[3] + c1[3] : c0[2] + c1[2];
                        const float scale = 0.08838834764831845f;
                        const uint32_t sp = pack_bf16(bf16r(d0) * scale, bf16r(d1) * scale);
                        if (diag) {
                            mx = fmaxf(mx, fmaxf(bf_lo(sp), bf_hi(sp)));
                            sts32(sc + (tile * 8 + g) * 4, sp);
                        }
                    }
                }
                {
#pragma unroll
                    for (int o = 16; o; o >>= 1) mx = fmaxf(mx, __shfl_xor_sync(0xffffffffu, mx, o));
                    if (lane == 0) sts32(red + cw * 4, __float_as_uint(mx));
                    bar_consumers();
                    const uint4 m0 = lds128(red), m1 = lds128(red + 16);
                    mx = fmaxf(fmaxf(fmaxf(__uint_as_float(m0.x), __uint_as_float(m0.y)), fmaxf(__uint_as_float(m0.z), __uint_as_float(m0.w))),
                               fmaxf(fmaxf(__uint_as_float(m1.x), __uint_as_float(m1.y)), fmaxf(__uint_as_float(m1.z), __uint_as_float(m1.w))));
                    const uint4 s0 = lds128(sc + lane * 16), s1 = lds128(sc + 512 + lane * 16);
                    const uint32_t w[8] = {s0.x, s0.y, s0.z, s0.w, s1.x, s1.y, s1.z, s1.w};
                    float e[16];
                    float sum = 0.f;
                    const float log2e = 1.4426950408889634f;
#pragma unroll
                    for (int i = 0; i < 8; i++) {
                        e[2 * i] = exp2f((bf_lo(w[i]) - mx) * log2e);
                        e[2 * i + 1] = exp2f((bf_hi(w[i]) - mx) * log2e);
                        sum += e[2 * i] + e[2 * i + 1];
                    }
#pragma unroll
                    for (int o = 16; o; o >>= 1) sum += __shfl_xor_sync(0xffffffffu, sum, o);
                    if (lane == 0) sts32(red + 32 + cw * 4, __float_as_uint(sum));
                    bar_consumers();
                    const uint4 t0 = lds128(red + 32), t1 = lds128(red + 48);
                    const float tot = ((__uint_as_float(t0.x) + __uint_as_float(t0.y)) + (__uint_as_float(t0.z) + __uint_as_float(t0.w))) +
                                      ((__uint_as_float(t1.x) + __uint_as_float(t1.y)) + (__uint_as_float(t1.z) + __uint_as_float(t1.w)));
                    const float inv = fdiv(1.0f, tot);
                    sts128(sc + lane * 16, pack_bf16(e[0] * inv, e[1] * inv), pack_bf16(e[2] * inv, e[3] * inv),
                           pack_bf16(e[4] * inv, e[5] * inv), pack_bf16(e[6] * inv, e[7] * inv));
                    sts128(sc + 512 + lane * 16, pack_bf16(e[8] * inv, e[9] * inv), pack_bf16(e[10] * inv, e[11] * inv),
                           pack_bf16(e[12] * inv, e[13] * inv), pack_bf16(e[14] * inv, e[15] * inv));
                    __syncwarp();
                }
                const int col = 64 * cw + 16 * t + g;
                float4* slot = g_acc + ((cta & 3) + 4 * bb) * 256 + cw * 32 + lane;
                unsigned short* outp = reinterpret_cast<unsigned short*>(p.out) + ((cta & 3) + 4 * bb) * kD + col;
                float x0 = __uint_as_float(lds16(sb + OFF_XR + bb * 1024 + col * 2) << 16);
                float x1 = __uint_as_float(lds16(sb + OFF_XR + bb * 1024 + col * 2 + 16) << 16);
                uint32_t ob_st = sb + OFF_OB + cw * OB_STRIDE + (16 * t + g) * 2;
                uint32_t ob_ld = sb + OFF_OB + r * OB_STRIDE + mi * 16;
                asm volatile("" : "+l"(slot), "+l"(outp), "+f"(x0), "+f"(x1), "+r"(ob_st), "+r"(ob_ld));
                float acc[8][4];
#pragma unroll
                for (int j = 0; j < 8; j++) acc[j][0] = acc[j][1] = acc[j][2] = acc[j][3] = 0.f;
                auto v_tile = [&](uint32_t pw, uint32_t st, uint32_t bar, uint32_t par, bool wait) {
                    uint32_t b0 = __byte_perm(pw, 0, sel0), b1 = __byte_perm(pw, 0, sel1);
                    const uint32_t base = ring.data0 + st * STAGE;
                    uint32_t va[4] = {base + voff, base + (voff ^ 32), base + (voff ^ 64), base + (voff ^ 96)};
                    asm volatile("" : "+r"(va[0]), "+r"(va[1]), "+r"(va[2]), "+r"(va[3]), "+r"(b0), "+r"(b1));
                    if (wait) mbar_wait(bar, par);
#pragma unroll
                    for (int jj = 0; jj < 8; jj++) {
                        const int j = 3 - (jj >> 1) + 4 * (jj & 1);
                        uint32_t a[4];
                        ldsm4t(a, va[j & 3] + (j >> 2) * 128);
                        mma16816(acc[j], a, b0, b1);
                    }
                };
#pragma unroll 1
                for (int tile = 0; tile < TILES - 2; tile++) {
                    if (tile == TILES - 3) mbar_wait(bar_gate, 0);
                    v_tile(lds32(sc + (tile * 8 + g) * 4), ring.st, ring.full0 + 8 * ring.st, ring.ph, true);
                    ring.release(lane);
                }
                {
                    const uint32_t pwa = lds32(sc + ((TILES - 2) * 8 + g) * 4), pwb = lds32(sc + ((TILES - 1) * 8 + g) * 4);
                    const uint32_t sta = ring.st, stb = sta + 1 == NST ? 0 : sta + 1;
                    const uint32_t bara = bb ? bar_last + 8 * cw : ring.full0 + 8 * sta;
                    const uint32_t barb = bb ? bar_last + 64 + 8 * cw : ring.full0 + 8 * stb;
                    const uint32_t para = bb ? 0 : ring.ph, parb = bb ? 0 : ring.ph ^ (stb == 0);
                    bool a_first;
                    uint32_t it = 0;
                    while (true) {
                        const bool ra = mbar_test(bara, para), rb = mbar_test(barb, parb);
                        a_first = __all_sync(0xffffffffu, ra);
                        if (a_first || __all_sync(0xffffffffu, rb) || ++it > kSpinLimit) break;
                    }
                    v_tile(a_first ? pwa : pwb, a_first ? sta : stb, 0, 0, false);
                    v_tile(a_first ? pwb : pwa, a_first ? stb : sta, a_first ? barb : bara, a_first ? parb : para, true);
                }
                {
                    float ev[8], od[8];
#pragma unroll
                    for (int j = 0; j < 8; j++) {
                        ev[j] = acc[j][0] + acc[j][3];
                        od[j] = acc[j][1] + acc[j][2];
                    }
#pragma unroll
                    for (int j = 0; j < 8; j += 2) {
                        ev[j] += __shfl_xor_sync(0xffffffffu, ev[j + 1], 1);
                        od[j] += __shfl_xor_sync(0xffffffffu, od[j + 1], 1);
                    }
#pragma unroll
                    for (int j = 0; j < 8; j += 4) {
                        ev[j] += __shfl_xor_sync(0xffffffffu, ev[j + 2], 2);
                        od[j] += __shfl_xor_sync(0xffffffffu, od[j + 2], 2);
                    }
                    sts16(ob_st, ev[0]);
                    sts16(ob_st + 16, od[0]);
                    sts16(ob_st + 128, ev[4]);
                    sts16(ob_st + 144, od[4]);
                }
                bar_consumers();
                {
                    float pc[4][4];
#pragma unroll
                    for (int mt = 0; mt < 4; mt++) pc[mt][0] = pc[mt][1] = pc[mt][2] = pc[mt][3] = 0.f;
#pragma unroll
                    for (int s2 = 0; s2 < 4; s2++) {
                        uint32_t b[4];
                        ldsm4(b, ob_ld + s2 * 64);
#pragma unroll
                        for (int mt = 0; mt < 4; mt++) mma16816(pc[mt], wo[2 * s2][mt], b[0], b[1]);
#pragma unroll
                        for (int mt = 0; mt < 4; mt++) mma16816(pc[mt], wo[2 * s2 + 1][mt], b[2], b[3]);
                    }
                    float lo[4], hi[4];
#pragma unroll
                    for (int mt = 0; mt < 4; mt++) {
                        lo[mt] = pc[mt][0] + pc[mt][1];
                        hi[mt] = pc[mt][2] + pc[mt][3];
                    }
                    const bool t1 = t & 1, t2 = t & 2;
                    const float yl0 = (t1 ? lo[1] : lo[0]) + __shfl_xor_sync(0xffffffffu, t1 ? lo[0] : lo[1], 1);
                    const float yl1 = (t1 ? lo[3] : lo[2]) + __shfl_xor_sync(0xffffffffu, t1 ? lo[2] : lo[3], 1);
                    const float yh0 = (t1 ? hi[1] : hi[0]) + __shfl_xor_sync(0xffffffffu, t1 ? hi[0] : hi[1], 1);
                    const float yh1 = (t1 ? hi[3] : hi[2]) + __shfl_xor_sync(0xffffffffu, t1 ? hi[2] : hi[3], 1);
                    const float zl = (t2 ? yl1 : yl0) + __shfl_xor_sync(0xffffffffu, t2 ? yl0 : yl1, 2);
                    const float zh = (t2 ? yh1 : yh0) + __shfl_xor_sync(0xffffffffu, t2 ? yh0 : yh1, 2);
                    const float4 prev = slot_arrive(slot, zl, zh);
                    ring.release(lane);
                    ring.release(lane);
                    slot_finish(prev, zl, zh, x0, x1, outp);
                }
            }
        } else {
            float ga[4][4], ua[4][4];
#pragma unroll
            for (int mt = 0; mt < 4; mt++)
#pragma unroll
                for (int i = 0; i < 4; i++) ga[mt][i] = ua[mt][i] = 0.f;
            const uint32_t xb = sb + OFF_XN + r * XN_STRIDE + mi * 16;
#pragma unroll 1
            for (int i = 0; i < 16; i++) {
                const uint32_t base = ring.acquire();
                if (cw < 7) gemm_block32(ga, base + cw * 4096, xb + i * 64, lane);
                ring.release(lane);
            }
#pragma unroll 1
            for (int i = 0; i < 16; i++) {
                const uint32_t base = ring.acquire();
                if (cw < 7) gemm_block32(ua, base + cw * 4096, xb + i * 64, lane);
                ring.release(lane);
            }
            const uint32_t hs = sb + OFF_SC;
            if (cw < 7) {
#pragma unroll
                for (int mt = 0; mt < 4; mt++)
#pragma unroll
                    for (int i = 0; i < 4; i++)
                        sts16(hs + (2 * t + (i & 1)) * HS_STRIDE + (64 * cw + 16 * mt + g + (i >> 1) * 8) * 2,
                              bf16r(ga[mt][i]) * bf16r(ua[mt][i]));
            }
            bar_consumers();
#pragma unroll
            for (int mt = 0; mt < 4; mt++)
#pragma unroll
                for (int i = 0; i < 4; i++) ga[mt][i] = 0.f;
#pragma unroll 1
            for (int i = 0; i < 14; i++) {
                const uint32_t base = ring.acquire();
                gemm_block32(ga, base + cw * 4096, hs + r * HS_STRIDE + mi * 16 + i * 64, lane);
                ring.release(lane);
            }
            const int j = cta - kAttnCtas;
#pragma unroll
            for (int e = 0; e < 2; e++) {
                float4* dst = reinterpret_cast<float4*>(g_glu + (j * kB + 2 * t + e) * 256 + cw * 32 + g * 4);
                dst[0] = make_float4(ga[0][e], ga[0][2 + e], ga[1][e], ga[1][2 + e]);
                dst[1] = make_float4(ga[2][e], ga[2][2 + e], ga[3][e], ga[3][2 + e]);
            }
            bar_consumers();
            if (tid == 128) {
                fence_gpu();
                red_inc(&g_sync[64], kStageWrap);
                uint32_t it = 0;
                while (load_relaxed(&g_sync[64]) < kGluCtas && ++it < kSleepLimit) __nanosleep(200);
                fence_gpu();
            }
            __syncwarp();
            bar_consumers();
            const int si = j * 512 + (tid - 128) * 2;
            float4 d = make_float4(0.f, 0.f, 0.f, 0.f);
#pragma unroll
            for (int k = 0; k < kGluCtas; k++) {
                const float4 v = __ldcg(reinterpret_cast<const float4*>(g_glu + k * kB * 256 + si));
                d.x += v.x; d.y += v.y; d.z += v.z; d.w += v.w;
            }
            const float dd[4] = {bf16r(d.x), bf16r(d.y), bf16r(d.z), bf16r(d.w)};
            float gb[4];
#pragma unroll
            for (int k = 0; k < 4; k++) gb[k] = (float)(pack_bf16(fdiv(dd[k], 1.0f + expf(-dd[k])), 0.f) & 0xffffu);
            g_acc[si] = make_float4(0.f, 0.f, gb[0], gb[1]);
            g_acc[si + 1] = make_float4(0.f, 0.f, gb[2], gb[3]);
            bar_consumers();
            if (tid == 128) {
                fence_gpu();
                red_inc(&g_sync[64], kStageWrap);
            }
        }
    }
}

typedef CUresult (*EncodeFn)(CUtensorMap*, CUtensorMapDataType, cuuint32_t, void*, const cuuint64_t*, const cuuint64_t*,
                             const cuuint32_t*, const cuuint32_t*, CUtensorMapInterleave, CUtensorMapSwizzle,
                             CUtensorMapL2promotion, CUtensorMapFloatOOBfill);

void encode_weight(EncodeFn fn, CUtensorMap* m, void* ptr, int rows, int cols, int box_rows, int box_grps) {
    cuuint64_t dims[3] = {64, (cuuint64_t)rows, (cuuint64_t)(cols / 64)};
    cuuint64_t strides[2] = {(cuuint64_t)cols * 2, 128};
    cuuint32_t box[3] = {64, (cuuint32_t)box_rows, (cuuint32_t)box_grps};
    cuuint32_t es[3] = {1, 1, 1};
    fn(m, CU_TENSOR_MAP_DATA_TYPE_BFLOAT16, 3, ptr, dims, strides, box, es, CU_TENSOR_MAP_INTERLEAVE_NONE,
       CU_TENSOR_MAP_SWIZZLE_128B, CU_TENSOR_MAP_L2_PROMOTION_NONE, CU_TENSOR_MAP_FLOAT_OOB_FILL_NONE);
}

}

extern "C" void kernel_launch(void* const* d_in, const int* in_sizes, int n_in, void* d_out, int out_size) {
    static EncodeFn encode = nullptr;
    static bool resident = false;
    if (!encode) {
        void* fn = nullptr;
        cudaDriverEntryPointQueryResult qr;
        cudaGetDriverEntryPoint("cuTensorMapEncodeTiled", &fn, cudaEnableDefault, &qr);
        encode = (EncodeFn)fn;
        cudaFuncSetAttribute(fused_decode_kernel<true>, cudaFuncAttributeMaxDynamicSharedMemorySize, SMEM_BYTES);
        cudaFuncSetAttribute(fused_decode_kernel<false>, cudaFuncAttributeMaxDynamicSharedMemorySize, SMEM_BYTES);
        int dev = 0, sms = 0;
        cudaGetDevice(&dev);
        cudaDeviceGetAttribute(&sms, cudaDevAttrMultiProcessorCount, dev);
        resident = sms >= kGrid;
    }
    Params p;
    p.x = (const __nv_bfloat16*)d_in[0];
    p.k = (const char*)d_in[1];
    p.v = (const char*)d_in[2];
    p.out = (__nv_bfloat16*)d_out;
    CUtensorMap tm_wq, tm_wo, tm_wg, tm_wu, tm_wd;
    encode_weight(encode, &tm_wq, d_in[3], kD, kH * kDh, 128, 2);
    encode_weight(encode, &tm_wo, d_in[4], kH * kDh, kD, 32, 8);
    encode_weight(encode, &tm_wg, d_in[6], kD, kF, 32, 7);
    encode_weight(encode, &tm_wu, d_in[7], kD, kF, 32, 7);
    encode_weight(encode, &tm_wd, d_in[8], kF, kD, 32, 8);
    if (resident)
        fused_decode_kernel<true><<<kGrid, kThreads, SMEM_BYTES>>>(p, tm_wq, tm_wo, tm_wg, tm_wu, tm_wd);
    else
        fused_decode_kernel<false><<<kGrid, kThreads, SMEM_BYTES>>>(p, tm_wq, tm_wo, tm_wg, tm_wu, tm_wd);
}
```
